```python
import torch

def _softmax(x, axis=-1):
    return torch.softmax(x, dim=axis)
def _gelu(x):
    return torch.nn.functional.gelu(x, approximate="tanh")
def _silu(x):
    return torch.nn.functional.silu(x)
def _sigmoid(x):
    return torch.sigmoid(x)
def _layernorm(x, axis=-1, eps=1e-5):
    m = x.mean(dim=axis, keepdim=True)
    v = x.var(dim=axis, keepdim=True, unbiased=False)
    return (x - m) / torch.sqrt(v + eps)
def _scatter_add(tgt, idx, src, axis=0):
    return tgt.clone().index_add_(axis, idx, src)
def _segment_sum(src, seg, n):
    out = torch.zeros((n,) + src.shape[1:], dtype=src.dtype)
    return out.index_add_(0, seg, src)
def _pad(x, pw):
    flat = tuple(v for pair in reversed(pw) for v in pair)
    return torch.nn.functional.pad(x, flat)

kernel_name = 'standalone__kv_cache_quant_int4_int2_kv_with_per_channel_or_per_token_scales__decode'

def setup_inputs():

    _w = (lambda a: (lambda t: t.to(torch.bfloat16) if t.is_floating_point() else t)(torch.as_tensor(a)))
    B = 2
    Sq = 1
    Skv = 32768
    Hq = 32
    Hkv = 8
    Dh = 128
    bits = 3
    G = 32
    if G <= 0 or G >= Skv:
        G = max(1, Skv // 2)
    Skv = (Skv // G) * G
    ngk = Skv // G
    qmax = (1 << bits) - 1
    return {
        "q": _w((lambda *s: torch.randn(*s, dtype=torch.bfloat16) * 1.6)(B, Hq, Sq, Dh)),
        "qk": _w(torch.randint(0, qmax + 1, (B, Hkv, Skv, Dh)).to(torch.int32)),
        "qv": _w(torch.randint(0, qmax + 1, (B, Hkv, Skv, Dh)).to(torch.int32)),
        "k_scales": _w(torch.abs((lambda *s: torch.randn(*s, dtype=torch.bfloat16) * 1.6)(B, Hkv, ngk, Dh)) * 0.05 + 0.02),
        "k_zeros": _w((lambda *s: torch.randn(*s, dtype=torch.bfloat16) * 1.6)(B, Hkv, ngk, Dh) + float(qmax) / 2.0),
        "v_scales": _w(torch.abs((lambda *s: torch.randn(*s, dtype=torch.bfloat16) * 0.05)(B, Hkv, Skv, 1)) * 0.05 + 0.02),
        "v_zeros": _w((lambda *s: torch.randn(*s, dtype=torch.bfloat16) * 0.05)(B, Hkv, Skv, 1) + float(qmax) / 2.0),
    }

def reference(q, qk, qv, k_scales, k_zeros, v_scales, v_zeros):
    B, Hq, Sq, Dh = q.shape
    Hkv, Skv = qk.shape[1], qk.shape[2]
    ngk = k_scales.shape[2]
    G = Skv // ngk
    ks = (lambda x, n, axis: torch.repeat_interleave(x, n, dim=axis))(k_scales, G, axis=2)
    kz = (lambda x, n, axis: torch.repeat_interleave(x, n, dim=axis))(k_zeros, G, axis=2)
    k = ((lambda x, dt: x.to(dt))(qk, q.dtype) - kz) * ks
    v = ((lambda x, dt: x.to(dt))(qv, q.dtype) - v_zeros) * v_scales
    rep = Hq // Hkv
    if rep > 1:
        k = (lambda x, n, axis: torch.repeat_interleave(x, n, dim=axis))(k, rep, axis=1)
        v = (lambda x, n, axis: torch.repeat_interleave(x, n, dim=axis))(v, rep, axis=1)
    scale = float(Dh) ** -0.5
    logits = torch.einsum("bhqd,bhkd->bhqk", q, k) * scale
    p = _softmax(logits, axis=-1)
    o = torch.einsum("bhqk,bhkd->bhqd", p, v)
    return o
```

```cpp
#include <cuda_runtime.h>
#include <cuda_bf16.h>
#include <stdint.h>

namespace {

constexpr int DH        = 128;
constexpr int SKV       = 32768;
constexpr int NKVH      = 16;
constexpr int REP       = 4;
constexpr int CPH       = 8;
constexpr int NCTA      = NKVH * CPH;
constexpr int TOK       = 64;
constexpr int TPH       = SKV / TOK;
constexpr int NIT       = TPH / CPH;
constexpr int NSTAGE    = 3;
constexpr int TILE_B    = TOK * DH * 4;
constexpr int KS_B      = (TOK / 32) * DH * 2;
constexpr int VS_B      = TOK * 2;
constexpr int SC_B      = 2 * KS_B + 2 * VS_B;
constexpr int Q_B       = REP * DH * 2;
constexpr int NCW       = 8;
constexpr int NTHREADS  = (NCW + 1) * 32;

constexpr int OFF_RING  = 0;
constexpr int OFF_SC    = OFF_RING + NSTAGE * 2 * TILE_B;
constexpr int OFF_Q     = OFF_SC + NSTAGE * SC_B;
constexpr int OFF_P     = OFF_Q + Q_B;
constexpr int OFF_ML    = OFF_P + NCW * 128;
constexpr int OFF_BAR   = OFF_ML + 2 * NCW * 16;
constexpr int OFF_FLAG  = OFF_BAR + NSTAGE * 32;
constexpr int SMEM_B    = OFF_FLAG + 16;

struct Partial { float o[REP][DH]; float m[REP]; float l[REP]; };

__device__ Partial      g_part[NKVH][CPH];
__device__ unsigned int g_cnt[NKVH * 32];

__device__ __forceinline__ void mbar_init(uint32_t bar, uint32_t cnt) {
    asm volatile("mbarrier.init.shared::cta.b64 [%0], %1;" :: "r"(bar), "r"(cnt) : "memory");
}
__device__ __forceinline__ void mbar_expect_tx(uint32_t bar, uint32_t bytes) {
    asm volatile("mbarrier.arrive.expect_tx.shared::cta.b64 _, [%0], %1;" :: "r"(bar), "r"(bytes) : "memory");
}
__device__ __forceinline__ void mbar_arrive(uint32_t bar) {
    asm volatile("mbarrier.arrive.shared::cta.b64 _, [%0];" :: "r"(bar) : "memory");
}
__device__ __forceinline__ void mbar_wait(uint32_t bar, uint32_t parity) {
    uint32_t done;
    #pragma unroll 1
    for (int it = 0; it < (1 << 24); it++) {
        asm volatile("{ .reg .pred p; mbarrier.try_wait.parity.shared::cta.b64 p, [%1], %2; selp.u32 %0, 1, 0, p; }"
                     : "=r"(done) : "r"(bar), "r"(parity) : "memory");
        if (done) return;
    }
    __trap();
}
__device__ __forceinline__ void bulk_g2s(uint32_t dst, const void* src, uint32_t bytes, uint32_t bar) {
    asm volatile("cp.async.bulk.shared::cluster.global.mbarrier::complete_tx::bytes [%0], [%1], %2, [%3];"
                 :: "r"(dst), "l"(src), "r"(bytes), "r"(bar) : "memory");
}
__device__ __forceinline__ int4 lds128i(uint32_t a) {
    int4 v; asm volatile("ld.shared.v4.s32 {%0,%1,%2,%3}, [%4];" : "=r"(v.x), "=r"(v.y), "=r"(v.z), "=r"(v.w) : "r"(a)); return v;
}
__device__ __forceinline__ float4 lds128f(uint32_t a) {
    float4 v; asm volatile("ld.shared.v4.f32 {%0,%1,%2,%3}, [%4];" : "=f"(v.x), "=f"(v.y), "=f"(v.z), "=f"(v.w) : "r"(a)); return v;
}
__device__ __forceinline__ uint2 lds64(uint32_t a) {
    uint2 v; asm volatile("ld.shared.v2.u32 {%0,%1}, [%2];" : "=r"(v.x), "=r"(v.y) : "r"(a)); return v;
}
__device__ __forceinline__ float lds_bf16(uint32_t a) {
    uint32_t v; asm volatile("ld.shared.u16 %0, [%1];" : "=r"(v) : "r"(a)); return __uint_as_float(v << 16);
}
__device__ __forceinline__ float bf_lo(uint32_t v) { return __uint_as_float(v << 16); }
__device__ __forceinline__ float bf_hi(uint32_t v) { return __uint_as_float(v & 0xffff0000u); }
__device__ __forceinline__ float ex2(float x) { float y; asm("ex2.approx.ftz.f32 %0, %1;" : "=f"(y) : "f"(x)); return y; }
__device__ __forceinline__ void cons_sync() { asm volatile("bar.sync 1, %0;" :: "n"(NCW * 32) : "memory"); }

__global__ void __launch_bounds__(NTHREADS, 1)
kv_decode_kernel(const char* __restrict__ q, const char* __restrict__ qk, const char* __restrict__ qv,
                 const char* __restrict__ ks, const char* __restrict__ kz,
                 const char* __restrict__ vs, const char* __restrict__ vz,
                 __nv_bfloat16* __restrict__ out, Partial* __restrict__ part, unsigned int* __restrict__ cnt)
{
    extern __shared__ __align__(128) char smem[];
    const uint32_t sb   = (uint32_t)__cvta_generic_to_shared(smem);
    const uint32_t bars = sb + OFF_BAR;
    const int tid  = threadIdx.x;
    const int head = blockIdx.x / CPH;
    const int sub  = blockIdx.x % CPH;
    const int tile0 = head * TPH + sub;

    auto issueK = [&](int tile, int s, uint32_t extra) {
        const uint32_t bar = bars + 32 * s;
        const uint32_t sc  = sb + OFF_SC + s * SC_B;
        mbar_expect_tx(bar, TILE_B + SC_B + extra);
        bulk_g2s(sb + OFF_RING + s * 2 * TILE_B, qk + (size_t)tile * TILE_B, TILE_B, bar);
        bulk_g2s(sc,                   ks + (size_t)tile * KS_B, KS_B, bar);
        bulk_g2s(sc + KS_B,            kz + (size_t)tile * KS_B, KS_B, bar);
        bulk_g2s(sc + 2 * KS_B,        vs + (size_t)tile * VS_B, VS_B, bar);
        bulk_g2s(sc + 2 * KS_B + VS_B, vz + (size_t)tile * VS_B, VS_B, bar);
    };
    auto issueV = [&](int tile, int s) {
        const uint32_t bar = bars + 32 * s + 8;
        mbar_expect_tx(bar, TILE_B);
        bulk_g2s(sb + OFF_RING + (s * 2 + 1) * TILE_B, qv + (size_t)tile * TILE_B, TILE_B, bar);
    };

    if (tid == NCW * 32) {
        #pragma unroll
        for (int s = 0; s < NSTAGE; s++) {
            mbar_init(bars + 32 * s, 1);
            mbar_init(bars + 32 * s + 8, 1);
            mbar_init(bars + 32 * s + 16, NCW);
            mbar_init(bars + 32 * s + 24, NCW);
        }
        asm volatile("fence.proxy.async.shared::cta;" ::: "memory");
        issueK(tile0, 0, Q_B);
        bulk_g2s(sb + OFF_Q, q + (size_t)head * Q_B, Q_B, bars);
        issueV(tile0, 0);
        #pragma unroll 1
        for (int s = 1; s < NSTAGE; s++) { issueK(tile0 + s * CPH, s, 0); issueV(tile0 + s * CPH, s); }
    }
    __syncthreads();

    if (tid >= NCW * 32) {
        if (tid == NCW * 32) {
            int s = 0, ph = 0;
            #pragma unroll 1
            for (int it = NSTAGE; it < NIT; it++) {
                const int tile = tile0 + it * CPH;
                mbar_wait(bars + 32 * s + 16, ph);
                issueK(tile, s, 0);
                mbar_wait(bars + 32 * s + 24, ph);
                issueV(tile, s);
                if (++s == NSTAGE) { s = 0; ph ^= 1; }
            }
        }
        return;
    }

    const int lane = tid & 31, w = tid >> 5;
    const int f = lane >> 2, g = lane & 3;

    float qr[REP][4];
    mbar_wait(bars, 0);
    {
        const float c = 0.08838834764831845f * 1.4426950408889634f;
        #pragma unroll
        for (int j = 0; j < REP; j++) {
            const uint2 v = lds64(sb + OFF_Q + (j ^ g) * (DH * 2) + lane * 8);
            qr[j][0] = bf_lo(v.x) * c; qr[j][1] = bf_hi(v.x) * c;
            qr[j][2] = bf_lo(v.y) * c; qr[j][3] = bf_hi(v.y) * c;
        }
    }

    float o[REP][4];
    #pragma unroll
    for (int h = 0; h < REP; h++) { o[h][0] = o[h][1] = o[h][2] = o[h][3] = 0.f; }
    float m = -INFINITY, l = 0.f, zs = 0.f;

    const uint32_t pbuf = sb + OFF_P + w * 128;
    int s = 0, ph = 0;
    #pragma unroll 1
    for (int it = 0; it < NIT; it++) {
        const uint32_t kb = sb + OFF_RING + s * 2 * TILE_B + w * (8 * 512) + lane * 16;
        const uint32_t sc = sb + OFF_SC + s * SC_B;
        mbar_wait(bars + 32 * s, ph);

        int4 kv[8];
        #pragma unroll
        for (int i = 0; i < 8; i++) kv[i] = lds128i(kb + ((i ^ f) << 9));
        const uint2 ks4 = lds64(sc + (w >> 2) * 256 + lane * 8);
        const uint2 kz4 = lds64(sc + KS_B + (w >> 2) * 256 + lane * 8);
        const float vs_t = lds_bf16(sc + 2 * KS_B + (w * 8 + f) * 2);
        const float vz_t = lds_bf16(sc + 2 * KS_B + VS_B + (w * 8 + f) * 2);
        __syncwarp();
        if (lane == 0) mbar_arrive(bars + 32 * s + 16);

        float qs[REP][4], nb[REP];
        {
            const float s0 = bf_lo(ks4.x), s1 = bf_hi(ks4.x), s2 = bf_lo(ks4.y), s3 = bf_hi(ks4.y);
            const float z0 = bf_lo(kz4.x), z1 = bf_hi(kz4.x), z2 = bf_lo(kz4.y), z3 = bf_hi(kz4.y);
            #pragma unroll
            for (int j = 0; j < REP; j++) {
                qs[j][0] = qr[j][0] * s0; qs[j][1] = qr[j][1] * s1;
                qs[j][2] = qr[j][2] * s2; qs[j][3] = qr[j][3] * s3;
                nb[j] = -(qs[j][0] * z0 + qs[j][1] * z1 + qs[j][2] * z2 + qs[j][3] * z3);
            }
        }
        float acc[8][REP];
        #pragma unroll
        for (int i = 0; i < 8; i++) {
            const float k0 = (float)kv[i].x, k1 = (float)kv[i].y, k2 = (float)kv[i].z, k3 = (float)kv[i].w;
            #pragma unroll
            for (int j = 0; j < REP; j++)
                acc[i][j] = fmaf(qs[j][3], k3, fmaf(qs[j][2], k2, fmaf(qs[j][1], k1, fmaf(qs[j][0], k0, nb[j]))));
        }
        #pragma unroll
        for (int i = 0; i < 4; i++)
            #pragma unroll
            for (int j = 0; j < REP; j++) acc[i][j] += __shfl_xor_sync(0xffffffffu, acc[i + 4][j], 16);
        #pragma unroll
        for (int i = 0; i < 2; i++)
            #pragma unroll
            for (int j = 0; j < REP; j++) acc[i][j] += __shfl_xor_sync(0xffffffffu, acc[i + 2][j], 8);
        #pragma unroll
        for (int j = 0; j < REP; j++) acc[0][j] += __shfl_xor_sync(0xffffffffu, acc[1][j], 4);
        acc[0][0] += __shfl_xor_sync(0xffffffffu, acc[0][2], 2);
        acc[0][1] += __shfl_xor_sync(0xffffffffu, acc[0][3], 2);
        const float sv = acc[0][0] + __shfl_xor_sync(0xffffffffu, acc[0][1], 1);

        if (__any_sync(0xffffffffu, sv > m)) {
            float mx = fmaxf(sv, __shfl_xor_sync(0xffffffffu, sv, 4));
            mx = fmaxf(mx, __shfl_xor_sync(0xffffffffu, mx, 8));
            mx = fmaxf(mx, __shfl_xor_sync(0xffffffffu, mx, 16));
            mx = fmaxf(mx, m);
            const float corr = ex2(m - mx);
            m = mx; l *= corr; zs *= corr;
            #pragma unroll
            for (int h = 0; h < REP; h++) {
                const float ch = __shfl_sync(0xffffffffu, corr, h);
                o[h][0] *= ch; o[h][1] *= ch; o[h][2] *= ch; o[h][3] *= ch;
            }
        }
        const float p = ex2(sv - m);
        const float pv = p * vs_t;
        l += p;
        zs = fmaf(pv, vz_t, zs);
        asm volatile("st.shared.f32 [%0], %1;" :: "r"(pbuf + lane * 4), "f"(pv) : "memory");
        __syncwarp();

        mbar_wait(bars + 32 * s + 8, ph);
        const uint32_t vb = kb + TILE_B;
        int4 vv[8];
        #pragma unroll
        for (int i = 0; i < 8; i++) vv[i] = lds128i(vb + (i << 9));
        float4 pp[8];
        #pragma unroll
        for (int i = 0; i < 8; i++) pp[i] = lds128f(pbuf + i * 16);
        __syncwarp();
        if (lane == 0) mbar_arrive(bars + 32 * s + 24);
        #pragma unroll
        for (int i = 0; i < 8; i++) {
            const float v0 = (float)vv[i].x, v1 = (float)vv[i].y, v2 = (float)vv[i].z, v3 = (float)vv[i].w;
            const float ph4[4] = {pp[i].x, pp[i].y, pp[i].z, pp[i].w};
            #pragma unroll
            for (int h = 0; h < REP; h++) {
                o[h][0] = fmaf(ph4[h], v0, o[h][0]); o[h][1] = fmaf(ph4[h], v1, o[h][1]);
                o[h][2] = fmaf(ph4[h], v2, o[h][2]); o[h][3] = fmaf(ph4[h], v3, o[h][3]);
            }
        }
        if (++s == NSTAGE) { s = 0; ph ^= 1; }
    }

    #pragma unroll
    for (int x = 4; x <= 16; x <<= 1) {
        l  += __shfl_xor_sync(0xffffffffu, l, x);
        zs += __shfl_xor_sync(0xffffffffu, zs, x);
    }
    float* sm_m = reinterpret_cast<float*>(smem + OFF_ML);
    float* sm_l = sm_m + NCW * REP;
    if (lane < REP) sm_m[w * REP + lane] = m;
    cons_sync();
    float M = sm_m[g];
    #pragma unroll
    for (int x = 1; x < NCW; x++) M = fmaxf(M, sm_m[x * REP + g]);
    const float cw = ex2(m - M);
    if (lane < REP) sm_l[w * REP + lane] = l * cw;
    float* red = reinterpret_cast<float*>(smem + OFF_RING);
    #pragma unroll
    for (int h = 0; h < REP; h++) {
        const float ch = __shfl_sync(0xffffffffu, cw, h), zh = __shfl_sync(0xffffffffu, zs, h);
        *reinterpret_cast<float4*>(red + (w * REP + h) * DH + lane * 4) =
            make_float4((o[h][0] - zh) * ch, (o[h][1] - zh) * ch, (o[h][2] - zh) * ch, (o[h][3] - zh) * ch);
    }
    cons_sync();
    Partial* mine = part + head * CPH + sub;
    {
        float2 a = make_float2(0.f, 0.f);
        #pragma unroll
        for (int x = 0; x < NCW; x++) {
            const float2 b = *reinterpret_cast<const float2*>(red + x * REP * DH + tid * 2);
            a.x += b.x; a.y += b.y;
        }
        __stcg(reinterpret_cast<float2*>(&mine->o[0][0]) + tid, a);
        if (tid < REP) {
            float L = 0.f;
            #pragma unroll
            for (int x = 0; x < NCW; x++) L += sm_l[x * REP + tid];
            __stcg(&mine->m[tid], M);
            __stcg(&mine->l[tid], L);
        }
    }
    __threadfence();
    cons_sync();
    volatile unsigned int* flag = reinterpret_cast<volatile unsigned int*>(smem + OFF_FLAG);
    if (tid == 0) {
        const unsigned int t = atomicAdd(&cnt[head * 32], 1u);
        if (t == CPH - 1) cnt[head * 32] = 0;
        *flag = t;
    }
    cons_sync();
    if (*flag != CPH - 1) return;
    __threadfence();

    {
        const int h = tid >> 6;
        const Partial* pp = part + head * CPH;
        float mm[CPH], ll[CPH]; float2 oo[CPH];
        #pragma unroll
        for (int x = 0; x < CPH; x++) {
            mm[x] = __ldcg(&pp[x].m[h]);
            ll[x] = __ldcg(&pp[x].l[h]);
            oo[x] = __ldcg(reinterpret_cast<const float2*>(&pp[x].o[0][0]) + tid);
        }
        float MM = mm[0];
        #pragma unroll
        for (int x = 1; x < CPH; x++) MM = fmaxf(MM, mm[x]);
        float L = 0.f, ax = 0.f, ay = 0.f;
        #pragma unroll
        for (int x = 0; x < CPH; x++) {
            const float c = ex2(mm[x] - MM);
            L = fmaf(ll[x], c, L); ax = fmaf(oo[x].x, c, ax); ay = fmaf(oo[x].y, c, ay);
        }
        const float inv = 1.0f / L;
        reinterpret_cast<__nv_bfloat162*>(out)[head * (REP * DH / 2) + tid] = __floats2bfloat162_rn(ax * inv, ay * inv);
    }
}

}

extern "C" void kernel_launch(void* const* d_in, const int* in_sizes, int n_in, void* d_out, int out_size) {
    (void)in_sizes; (void)n_in; (void)out_size;
    static Partial* part = nullptr;
    static unsigned int* cnt = nullptr;
    if (!part) {
        cudaFuncSetAttribute(kv_decode_kernel, cudaFuncAttributeMaxDynamicSharedMemorySize, SMEM_B);
        cudaGetSymbolAddress((void**)&part, g_part);
        cudaGetSymbolAddress((void**)&cnt, g_cnt);
    }
    kv_decode_kernel<<<NCTA, NTHREADS, SMEM_B>>>(
        (const char*)d_in[0], (const char*)d_in[1], (const char*)d_in[2], (const char*)d_in[3],
        (const char*)d_in[4], (const char*)d_in[5], (const char*)d_in[6], (__nv_bfloat16*)d_out, part, cnt);
}
```

```cpp
#include <cuda_runtime.h>
#include <cuda_bf16.h>
#include <stdint.h>

#define PACE_X 64
#define LEAD_ 4
#define NPRE_ 2
#define WARM 1
#define STAG 0
#define EVF 1

#define TL(i)

namespace {

constexpr int DH        = 128;
constexpr int SKV       = 32768;
constexpr int NKVH      = 16;
constexpr int REP       = 4;
constexpr int CPH       = 8;
constexpr int NCTA      = NKVH * CPH;
constexpr int TOK       = 32;
constexpr int TPH       = SKV / TOK;
constexpr int NIT       = TPH / CPH;
constexpr int NSTAGE    = 6;
constexpr int LEAD      = LEAD_;
constexpr int NPRE      = NPRE_;
constexpr int TILE_B    = TOK * DH * 4;
constexpr int KS_B      = DH * 2;
constexpr int VS_B      = TOK * 2;
constexpr int SC_B      = 2 * KS_B + 2 * VS_B;
constexpr int Q_B       = REP * DH * 2;
constexpr int NCW       = 8;
constexpr int NFW       = 4;
constexpr int NTHREADS  = (NCW + NFW + 1) * 32;
static_assert(NPRE + LEAD <= NSTAGE && (LEAD == 2 || LEAD == 4), "ring too small");

constexpr int OFF_K     = 0;
constexpr int OFF_V     = OFF_K + NSTAGE * TILE_B;
constexpr int OFF_RED   = OFF_V + NSTAGE * TILE_B;
constexpr int OFF_SC    = OFF_RED + NCW * REP * DH * 4;
constexpr int OFF_Q     = OFF_SC + NSTAGE * SC_B;
constexpr int OFF_P     = OFF_Q + Q_B;
constexpr int OFF_ML    = OFF_P + NCW * 128;
constexpr int OFF_BAR   = OFF_ML + 3 * NCW * REP * 4;
constexpr int OFF_TL    = OFF_BAR + NSTAGE * 32;
constexpr int SMEM_B    = OFF_TL + 128;

struct __align__(128) Inbox {
    float o[CPH][64];
    float ml[CPH][32];
};
struct Scratch {
    Inbox        inbox[NCTA];
    unsigned int pace[32];
    unsigned int ready[NKVH][32];
};
__device__ Scratch g_scratch;

__device__ __forceinline__ void mbar_init(uint32_t bar, uint32_t cnt) {
    asm volatile("mbarrier.init.shared::cta.b64 [%0], %1;" :: "r"(bar), "r"(cnt) : "memory");
}
__device__ __forceinline__ void mbar_expect_tx(uint32_t bar, uint32_t bytes) {
    asm volatile("mbarrier.arrive.expect_tx.shared::cta.b64 _, [%0], %1;" :: "r"(bar), "r"(bytes) : "memory");
}
__device__ __forceinline__ void mbar_arrive_if(int on, uint32_t bar) {
    asm volatile("{ .reg .pred p; setp.ne.s32 p, %0, 0; @p mbarrier.arrive.shared::cta.b64 _, [%1]; }" :: "r"(on), "r"(bar) : "memory");
}
__device__ __forceinline__ void mbar_wait(uint32_t bar, uint32_t parity) {
    asm volatile("{\n"
                 ".reg .pred p;\n"
                 ".reg .u32 n;\n"
                 "mov.u32 n, 0;\n"
                 "WAIT:\n"
                 "mbarrier.try_wait.parity.shared::cta.b64 p, [%0], %1;\n"
                 "@p bra.uni DONE;\n"
                 "add.u32 n, n, 1;\n"
                 "setp.lt.u32 p, n, 0x1000000;\n"
                 "@p bra.uni WAIT;\n"
                 "trap;\n"
                 "DONE:\n"
                 "}" :: "r"(bar), "r"(parity) : "memory");
}
__device__ __forceinline__ void bulk_g2s(uint32_t dst, const void* src, uint32_t bytes, uint32_t bar, uint64_t pol) {
    asm volatile("cp.async.bulk.shared::cluster.global.mbarrier::complete_tx::bytes.L2::cache_hint [%0], [%1], %2, [%3], %4;"
                 :: "r"(dst), "l"(src), "r"(bytes), "r"(bar), "l"(pol) : "memory");
}
__device__ __forceinline__ uint32_t atom_inc(unsigned int* p, uint32_t wrap) {
    uint32_t r; asm volatile("atom.relaxed.gpu.global.inc.u32 %0, [%1], %2;" : "=r"(r) : "l"(p), "r"(wrap) : "memory"); return r;
}
__device__ __forceinline__ void red_inc(unsigned int* p, uint32_t wrap) {
    asm volatile("red.relaxed.gpu.global.inc.u32 [%0], %1;" :: "l"(p), "r"(wrap) : "memory");
}
__device__ __forceinline__ uint32_t ld_relaxed(const unsigned int* p) {
    uint32_t r; asm volatile("ld.relaxed.gpu.global.u32 %0, [%1];" : "=r"(r) : "l"(p) : "memory"); return r;
}
__device__ __forceinline__ uint32_t ld_acquire(const unsigned int* p) {
    uint32_t r; asm volatile("ld.acquire.gpu.global.u32 %0, [%1];" : "=r"(r) : "l"(p) : "memory"); return r;
}
__device__ __forceinline__ int4 lds128i(uint32_t a) {
    int4 v; asm volatile("ld.shared.v4.s32 {%0,%1,%2,%3}, [%4];" : "=r"(v.x), "=r"(v.y), "=r"(v.z), "=r"(v.w) : "r"(a)); return v;
}
__device__ __forceinline__ float4 lds128f(uint32_t a) {
    float4 v; asm volatile("ld.shared.v4.f32 {%0,%1,%2,%3}, [%4];" : "=f"(v.x), "=f"(v.y), "=f"(v.z), "=f"(v.w) : "r"(a)); return v;
}
__device__ __forceinline__ void sts128f(uint32_t a, float x, float y, float z, float w) {
    asm volatile("st.shared.v4.f32 [%0], {%1,%2,%3,%4};" :: "r"(a), "f"(x), "f"(y), "f"(z), "f"(w) : "memory");
}
__device__ __forceinline__ void sts32f(uint32_t a, float x) {
    asm volatile("st.shared.f32 [%0], %1;" :: "r"(a), "f"(x) : "memory");
}
__device__ __forceinline__ uint2 lds64(uint32_t a) {
    uint2 v; asm volatile("ld.shared.v2.u32 {%0,%1}, [%2];" : "=r"(v.x), "=r"(v.y) : "r"(a)); return v;
}
__device__ __forceinline__ float lds_bf16(uint32_t a) {
    uint32_t v; asm volatile("ld.shared.u16 %0, [%1];" : "=r"(v) : "r"(a)); return __uint_as_float(v << 16);
}
__device__ __forceinline__ float bf_lo(uint32_t v) { return __uint_as_float(v << 16); }
__device__ __forceinline__ float bf_hi(uint32_t v) { return __uint_as_float(v & 0xffff0000u); }
__device__ __forceinline__ float ex2(float x) { float y; asm("ex2.approx.ftz.f32 %0, %1;" : "=f"(y) : "f"(x)); return y; }
__device__ __forceinline__ uint32_t nz(float x) { return max(__float_as_uint(x), 1u); }

template <int ID, int N> __device__ __forceinline__ void bar_sync_if(int on) {
    asm volatile("{ .reg .pred p; setp.ne.s32 p, %0, 0; @p bar.sync %1, %2; }" :: "r"(on), "n"(ID), "n"(N) : "memory");
}
template <int ID, int N> __device__ __forceinline__ void bar_arrive_if(int on) {
    asm volatile("{ .reg .pred p; setp.ne.s32 p, %0, 0; @p bar.arrive %1, %2; }" :: "r"(on), "n"(ID), "n"(N) : "memory");
}
__device__ __forceinline__ void stg128_if(int on, void* p, uint32_t x, uint32_t y, uint32_t z, uint32_t w) {
    asm volatile("{ .reg .pred p; setp.ne.s32 p, %0, 0; @p st.relaxed.gpu.global.v4.u32 [%1], {%2,%3,%4,%5}; }"
                 :: "r"(on), "l"(p), "r"(x), "r"(y), "r"(z), "r"(w) : "memory");
}
__device__ __forceinline__ void stg64_if(int on, void* p, uint32_t x, uint32_t y) {
    asm volatile("{ .reg .pred p; setp.ne.s32 p, %0, 0; @p st.relaxed.gpu.global.v2.u32 [%1], {%2,%3}; }"
                 :: "r"(on), "l"(p), "r"(x), "r"(y) : "memory");
}
__device__ __forceinline__ void stg32_if(int on, void* p, uint32_t x) {
    asm volatile("{ .reg .pred p; setp.ne.s32 p, %0, 0; @p st.global.u32 [%1], %2; }" :: "r"(on), "l"(p), "r"(x) : "memory");
}
__device__ __forceinline__ void ldg128_if(int on, const void* p, uint4& v) {
    asm volatile("{ .reg .pred p; setp.ne.s32 p, %4, 0; @p ld.relaxed.gpu.global.v4.u32 {%0,%1,%2,%3}, [%5]; }"
                 : "+r"(v.x), "+r"(v.y), "+r"(v.z), "+r"(v.w) : "r"(on), "l"(p) : "memory");
}
__device__ __forceinline__ void ldg64_if(int on, const void* p, uint2& v) {
    asm volatile("{ .reg .pred p; setp.ne.s32 p, %2, 0; @p ld.relaxed.gpu.global.v2.u32 {%0,%1}, [%3]; }"
                 : "+r"(v.x), "+r"(v.y) : "r"(on), "l"(p) : "memory");
}

constexpr int BAR_ML = 2;
constexpr int BAR_A  = 3;
constexpr int BAR_O  = 4;
constexpr int BAR_F  = 5;
constexpr int BAR_Z  = 6;

__global__ void __launch_bounds__(NTHREADS, 1)
kv_decode_kernel(const char* __restrict__ q, const char* __restrict__ qk, const char* __restrict__ qv,
                 const char* __restrict__ ks, const char* __restrict__ kz,
                 const char* __restrict__ vs, const char* __restrict__ vz,
                 __nv_bfloat16* __restrict__ out, Scratch* __restrict__ scr, int first_pass)
{
    extern __shared__ __align__(128) char smem[];
    const uint32_t sb   = (uint32_t)__cvta_generic_to_shared(smem);
    const uint32_t bars = sb + OFF_BAR;
    const int tid  = threadIdx.x;
    const int head = blockIdx.x / CPH;
    const int sub  = blockIdx.x % CPH;
    const int tile0 = head * TPH + sub;

    uint64_t pol;
    asm volatile("createpolicy.fractional.L2::evict_first.b64 %0, 1.0;" : "=l"(pol));
    auto issueK = [&](int tile, int s) {
        bulk_g2s(sb + OFF_K + s * TILE_B, qk + (size_t)tile * TILE_B, TILE_B, bars + 32 * s, pol);
    };
    auto issueS = [&](int tile, int s) {
        const uint32_t bar = bars + 32 * s;
        const uint32_t sc  = sb + OFF_SC + s * SC_B;
        bulk_g2s(sc,                   ks + (size_t)tile * KS_B, KS_B, bar, pol);
        bulk_g2s(sc + KS_B,            kz + (size_t)tile * KS_B, KS_B, bar, pol);
        bulk_g2s(sc + 2 * KS_B,        vs + (size_t)tile * VS_B, VS_B, bar, pol);
        bulk_g2s(sc + 2 * KS_B + VS_B, vz + (size_t)tile * VS_B, VS_B, bar, pol);
    };
    auto issueV = [&](int tile, int s) {
        mbar_expect_tx(bars + 32 * s + 8, TILE_B);
        bulk_g2s(sb + OFF_V + s * TILE_B, qv + (size_t)tile * TILE_B, TILE_B, bars + 32 * s + 8, pol);
    };

    if (tid == NTHREADS - 32) {
        mbar_init(bars, 1);
        mbar_init(bars + 32, 1);
        asm volatile("fence.proxy.async.shared::cta;" ::: "memory");
        mbar_expect_tx(bars, TILE_B + SC_B + Q_B);
        issueK(tile0, 0);
        mbar_expect_tx(bars + 32, TILE_B + SC_B);
        issueK(tile0 + CPH, 1);
        #pragma unroll
        for (int s = 0; s < NSTAGE; s++) {
            if (s >= 2) mbar_init(bars + 32 * s, 1);
            mbar_init(bars + 32 * s + 8, 1);
            mbar_init(bars + 32 * s + 16, NCW / 2);
            mbar_init(bars + 32 * s + 24, NCW / 2);
        }
        asm volatile("fence.proxy.async.shared::cta;" ::: "memory");
    }
    __syncthreads();
    const int lane = tid & 31;
    const int w = __shfl_sync(0xffffffffu, tid >> 5, 0);

    if (w == NCW + NFW) {
        if (lane == 0) {
            bulk_g2s(sb + OFF_Q, q + (size_t)head * Q_B, Q_B, bars, pol);
            #pragma unroll 1
            for (int s = 0; s < NPRE + LEAD; s++) {
                if (s >= 2) { mbar_expect_tx(bars + 32 * s, TILE_B + SC_B); issueK(tile0 + s * CPH, s); }
                issueS(tile0 + s * CPH, s);
                if (s >= LEAD) issueV(tile0 + (s - LEAD) * CPH, s - LEAD);
            }
            constexpr int NSTEP = NIT - LEAD - NPRE + LEAD / 2;
            int sk = (NPRE + LEAD) % NSTAGE, phk = ((NPRE + LEAD) / NSTAGE) ^ 1;
            int sv = NPRE, phv = 1;
            uint32_t pend = 0;
            int seen = 0, need = -PACE_X, budget = 1 << 16;
            #pragma unroll 1
            for (int it = NPRE; it < NIT; it++) {
                const bool hasK = it + LEAD < NIT;
                if (hasK) mbar_wait(bars + 32 * sk + 16, phk);
                if (it == NIT / 2) {
                    int n = 0;
                    while (ld_acquire(scr->ready[head]) < CPH) if (++n > (1 << 22)) __trap();
                    red_inc(scr->ready[head], 2 * CPH - 1);
                }
                if (hasK || !(it & 1)) {
                    if (seen < need) {
                        seen = (int)pend;
                        while (seen < need && budget > 0) { seen = (int)ld_relaxed(scr->pace); budget--; }
                    }
                    pend = atom_inc(scr->pace, NSTEP * NCTA - 1);
                    need += NCTA;
                }
                if (hasK) {
                    mbar_expect_tx(bars + 32 * sk, TILE_B + SC_B);
                    issueK(tile0 + (it + LEAD) * CPH, sk);
                    issueS(tile0 + (it + LEAD) * CPH, sk);
                }
                mbar_wait(bars + 32 * sv + 24, phv);
                issueV(tile0 + it * CPH, sv);
                if (++sk == NSTAGE) { sk = 0; phk ^= 1; }
                if (++sv == NSTAGE) { sv = 0; phv ^= 1; }
            }
        }
        return;
    }

    if (w >= NCW) {
        const int fw = w - NCW, src = lane >> 2, col = lane & 3;
        Inbox* in = &scr->inbox[blockIdx.x];
        stg128_if(1, &in->o[0][0] + (fw * 32 + lane) * 4, 0, 0, 0, 0);
        stg64_if(1, &in->ml[0][0] + (fw * 32 + lane) * 2, 0, 0);
        __threadfence();
        bar_sync_if<BAR_Z, NFW * 32>(1);
        if (fw == 0 && lane == 0) red_inc(scr->ready[head], 2 * CPH - 1);

        const float* pml = &in->ml[src][0];
        const float* po  = &in->o[src][(fw * 4 + col) * 4];
        #pragma unroll 1
        for (int pass = first_pass; pass < 2; pass++) {
            bar_sync_if<BAR_ML, (NCW + NFW) * 32>(pass);
            uint2 ml = make_uint2(0, 0);
            int guard = 0;
            do {
                ldg64_if(pass, pml, ml);
                if (++guard > (1 << 22)) __trap();
            } while (__any_sync(0xffffffffu, pass && !(ml.x && ml.y)));
            if (fw == 0) TL(12);
            const float ms = __uint_as_float(ml.x);
            float M = ms;
            #pragma unroll
            for (int x = 4; x <= 16; x <<= 1) M = fmaxf(M, __shfl_xor_sync(0xffffffffu, M, x));
            float cs = ex2(ms - M);
            float L = __uint_as_float(ml.y) * cs;
            #pragma unroll
            for (int x = 4; x <= 16; x <<= 1) L += __shfl_xor_sync(0xffffffffu, L, x);
            cs = __fdividef(cs, L);
            bar_sync_if<BAR_F, (NCW / 2 + NFW) * 32>(pass | (__float_as_uint(cs) == 0xffc12345u));
            uint4 a = make_uint4(0, 0, 0, 0);
            do {
                ldg128_if(pass, po, a);
                if (++guard > (1 << 22)) __trap();
            } while (__any_sync(0xffffffffu, pass && !(a.x && a.y && a.z && a.w)));
            if (fw == 0) TL(13);
            const float r0 = __uint_as_float(a.x) * cs, r1 = __uint_as_float(a.y) * cs;
            const float r2 = __uint_as_float(a.z) * cs, r3 = __uint_as_float(a.w) * cs;
            const bool hi = lane & 16;
            float y0 = (hi ? r2 : r0) + __shfl_xor_sync(0xffffffffu, hi ? r0 : r2, 16);
            float y1 = (hi ? r3 : r1) + __shfl_xor_sync(0xffffffffu, hi ? r1 : r3, 16);
            y0 += __shfl_xor_sync(0xffffffffu, y0, 8);
            y1 += __shfl_xor_sync(0xffffffffu, y1, 8);
            y0 += __shfl_xor_sync(0xffffffffu, y0, 4);
            y1 += __shfl_xor_sync(0xffffffffu, y1, 4);
            const __nv_bfloat162 y = __floats2bfloat162_rn(y0, y1);
            stg32_if(pass && (lane & 12) == 0, out + blockIdx.x * 64 + (fw * 4 + col) * 4 + (lane >> 4) * 2,
                     *reinterpret_cast<const uint32_t*>(&y));
            if (fw == 0) TL(14);
        }
        return;
    }

    const int f = lane >> 2, g = lane & 3;
    const int set = w >> 2, wq = w & 3;
    const uint32_t pbuf = sb + OFF_P + w * 128;
    Inbox* dst = &scr->inbox[head * CPH + 2 * wq + (lane >> 4)];

    #pragma unroll 1
    for (int pass = first_pass; pass < 2; pass++) {
        float o[REP][4];
        #pragma unroll
        for (int h = 0; h < REP; h++) { o[h][0] = o[h][1] = o[h][2] = o[h][3] = 0.f; }

        if (pass) {
            float qr[REP][4];
            mbar_wait(bars, 0);
            if (w == 0) TL(1);
            {
                const float c = 0.08838834764831845f * 1.4426950408889634f;
                #pragma unroll
                for (int j = 0; j < REP; j++) {
                    const uint2 v = lds64(sb + OFF_Q + (j ^ g) * (DH * 2) + lane * 8);
                    qr[j][0] = bf_lo(v.x) * c; qr[j][1] = bf_hi(v.x) * c;
                    qr[j][2] = bf_lo(v.y) * c; qr[j][3] = bf_hi(v.y) * c;
                }
            }
            float m = -INFINITY, l = 0.f, zs = 0.f;
            float pv0 = 0.f, co0 = 1.f, pv1 = 0.f, co1 = 1.f;
            int sk = set, phk = 0, sv = set, phv = 0;
            #pragma unroll 1
            for (int it = 0; it < NIT / 2 + LEAD / 2; it++) {
                const float pv_use = pv0, co_use = co0;
                if (LEAD == 4) { pv0 = pv1; co0 = co1; }
                if (it < NIT / 2) {
                    const uint32_t kb = sb + OFF_K + sk * TILE_B + wq * (8 * 512) + lane * 16;
                    const uint32_t sc = sb + OFF_SC + sk * SC_B;
                    mbar_wait(bars + 32 * sk, phk);
                    if (w == 4) TL(2);

                    const uint2 ks4 = lds64(sc + lane * 8);
                    const uint2 kz4 = lds64(sc + KS_B + lane * 8);
                    int4 kv[8];
                    #pragma unroll
                    for (int i = 0; i < 8; i++) kv[i] = lds128i(kb + ((i ^ f) << 9));
                    const float vs_t = lds_bf16(sc + 2 * KS_B + (wq * 8 + f) * 2);
                    const float vz_t = lds_bf16(sc + 2 * KS_B + VS_B + (wq * 8 + f) * 2);

                    float qs[REP][4], nb[REP];
                    {
                        const float s0 = bf_lo(ks4.x), s1 = bf_hi(ks4.x), s2 = bf_lo(ks4.y), s3 = bf_hi(ks4.y);
                        const float z0 = bf_lo(kz4.x), z1 = bf_hi(kz4.x), z2 = bf_lo(kz4.y), z3 = bf_hi(kz4.y);
                        #pragma unroll
                        for (int j = 0; j < REP; j++) {
                            qs[j][0] = qr[j][0] * s0; qs[j][1] = qr[j][1] * s1;
                            qs[j][2] = qr[j][2] * s2; qs[j][3] = qr[j][3] * s3;
                            nb[j] = -(qs[j][0] * z0 + qs[j][1] * z1 + qs[j][2] * z2 + qs[j][3] * z3);
                        }
                    }
                    float acc[8][REP];
                    #pragma unroll
                    for (int i = 0; i < 8; i++) {
                        const float k0 = (float)kv[i].x, k1 = (float)kv[i].y, k2 = (float)kv[i].z, k3 = (float)kv[i].w;
                        #pragma unroll
                        for (int j = 0; j < REP; j++)
                            acc[i][j] = fmaf(qs[j][3], k3, fmaf(qs[j][2], k2, fmaf(qs[j][1], k1, fmaf(qs[j][0], k0, nb[j]))));
                    }
                    #pragma unroll
                    for (int i = 0; i < 4; i++)
                        #pragma unroll
                        for (int j = 0; j < REP; j++) acc[i][j] += __shfl_xor_sync(0xffffffffu, acc[i + 4][j], 16);
                    #pragma unroll
                    for (int i = 0; i < 2; i++)
                        #pragma unroll
                        for (int j = 0; j < REP; j++) acc[i][j] += __shfl_xor_sync(0xffffffffu, acc[i + 2][j], 8);
                    #pragma unroll
                    for (int j = 0; j < REP; j++) acc[0][j] += __shfl_xor_sync(0xffffffffu, acc[1][j], 4);
                    acc[0][0] += __shfl_xor_sync(0xffffffffu, acc[0][2], 2);
                    acc[0][1] += __shfl_xor_sync(0xffffffffu, acc[0][3], 2);
                    const float lg = acc[0][0] + __shfl_xor_sync(0xffffffffu, acc[0][1], 1);
                    __syncwarp();
                    mbar_arrive_if(lane == 0, bars + 32 * sk + 16);
                    sk += 2;
                    if (sk >= NSTAGE) { sk -= NSTAGE; phk ^= 1; }

                    float corr = 1.f;
                    if (__any_sync(0xffffffffu, lg > m)) {
                        float mx = fmaxf(lg, __shfl_xor_sync(0xffffffffu, lg, 4));
                        mx = fmaxf(mx, __shfl_xor_sync(0xffffffffu, mx, 8));
                        mx = fmaxf(mx, __shfl_xor_sync(0xffffffffu, mx, 16));
                        mx = fmaxf(mx, m);
                        corr = ex2(m - mx);
                        m = mx; l *= corr; zs *= corr;
                    }
                    const float p = ex2(lg - m);
                    const float pv = p * vs_t;
                    l += p;
                    zs = fmaf(pv, vz_t, zs);
                    if (LEAD == 4) { pv1 = pv; co1 = corr; } else { pv0 = pv; co0 = corr; }

                    if (it == NIT / 2 - 1 || (WARM && it == 0)) {
                        float lt = l, zt = zs;
                        #pragma unroll
                        for (int x = 4; x <= 16; x <<= 1) {
                            lt += __shfl_xor_sync(0xffffffffu, lt, x);
                            zt += __shfl_xor_sync(0xffffffffu, zt, x);
                        }
                        if (f < 3) sts32f(sb + OFF_ML + (f * REP * NCW + g * NCW + w) * 4, f == 0 ? m : (f == 1 ? lt : zt));
                        __syncwarp();
                        bar_arrive_if<BAR_ML, (NCW + NFW) * 32>(set == 1 && it != 0);
                    }
                    if (w == 4) TL(3);
                }
                if (set == 0 && (it == NIT / 2 || (WARM && it == 0))) {
                    bar_sync_if<BAR_ML, (NCW + NFW) * 32>(it != 0);
                    const float4 ma = lds128f(sb + OFF_ML + wq * 32), mb = lds128f(sb + OFF_ML + wq * 32 + 16);
                    const float4 la = lds128f(sb + OFF_ML + 128 + wq * 32), lb = lds128f(sb + OFF_ML + 128 + wq * 32 + 16);
                    const float M = fmaxf(fmaxf(fmaxf(ma.x, ma.y), fmaxf(ma.z, ma.w)), fmaxf(fmaxf(mb.x, mb.y), fmaxf(mb.z, mb.w)));
                    const float L = la.x * ex2(ma.x - M) + la.y * ex2(ma.y - M) + la.z * ex2(ma.z - M) + la.w * ex2(ma.w - M)
                                  + lb.x * ex2(mb.x - M) + lb.y * ex2(mb.y - M) + lb.z * ex2(mb.z - M) + lb.w * ex2(mb.w - M);
                    stg64_if(it != 0 && (lane & 15) == 0, &dst->ml[sub][0], nz(M), nz(L));
                    if (w == 0) TL(6);
                }
                if (it >= LEAD / 2) {
                    sts32f(pbuf + lane * 4, pv_use);
                    if (__any_sync(0xffffffffu, co_use != 1.f)) {
                        #pragma unroll
                        for (int h = 0; h < REP; h++) {
                            const float ch = __shfl_sync(0xffffffffu, co_use, h);
                            o[h][0] *= ch; o[h][1] *= ch; o[h][2] *= ch; o[h][3] *= ch;
                        }
                    }
                    __syncwarp();
                    float4 pp[8];
                    #pragma unroll
                    for (int i = 0; i < 8; i++) pp[i] = lds128f(pbuf + i * 16);
                    const uint32_t vb = sb + OFF_V + sv * TILE_B + wq * (8 * 512) + lane * 16;
                    const uint32_t vbar = bars + 32 * sv + 8;
                    const int ph = phv;
                    sv += 2;
                    if (sv >= NSTAGE) { sv -= NSTAGE; phv ^= 1; }

                    mbar_wait(vbar, ph);
                    if (w == 4) TL(4);
                    int4 vv[8];
                    #pragma unroll
                    for (int i = 0; i < 8; i++) vv[i] = lds128i(vb + (i << 9));
                    #pragma unroll
                    for (int i = 0; i < 8; i++) {
                        const float v0 = (float)vv[i].x, v1 = (float)vv[i].y, v2 = (float)vv[i].z, v3 = (float)vv[i].w;
                        const float ph4[4] = {pp[i].x, pp[i].y, pp[i].z, pp[i].w};
                        #pragma unroll
                        for (int h = 0; h < REP; h++) {
                            o[h][0] = fmaf(ph4[h], v0, o[h][0]); o[h][1] = fmaf(ph4[h], v1, o[h][1]);
                            o[h][2] = fmaf(ph4[h], v2, o[h][2]); o[h][3] = fmaf(ph4[h], v3, o[h][3]);
                        }
                    }
                    asm volatile("" : "+f"(o[3][3]), "+f"(o[0][0]) :: "memory");
                    __syncwarp();
                    mbar_arrive_if(lane == 0, vbar + 16);
                }
            }
        }

        const uint32_t red = sb + OFF_RED + lane * 16;
        #pragma unroll
        for (int h = 0; h < REP; h++) sts128f(red + (w * REP + h) * (DH * 4), o[h][0], o[h][1], o[h][2], o[h][3]);
        bar_arrive_if<BAR_O, NCW * 32>(pass && set == 1);
        bar_arrive_if<BAR_F, (NCW / 2 + NFW) * 32>(pass && set == 1);
        if (w == 4) TL(5);
        if (set == 1) continue;

        if (w == 0) TL(7);
        const float4 ma = lds128f(sb + OFF_ML + wq * 32), mb = lds128f(sb + OFF_ML + wq * 32 + 16);
        const float4 za = lds128f(sb + OFF_ML + 256 + wq * 32), zb = lds128f(sb + OFF_ML + 256 + wq * 32 + 16);
        const float M = fmaxf(fmaxf(fmaxf(ma.x, ma.y), fmaxf(ma.z, ma.w)), fmaxf(fmaxf(mb.x, mb.y), fmaxf(mb.z, mb.w)));
        const float c[NCW] = {ex2(ma.x - M), ex2(ma.y - M), ex2(ma.z - M), ex2(ma.w - M),
                              ex2(mb.x - M), ex2(mb.y - M), ex2(mb.z - M), ex2(mb.w - M)};
        const float Z = za.x * c[0] + za.y * c[1] + za.z * c[2] + za.w * c[3] + zb.x * c[4] + zb.y * c[5] + zb.z * c[6] + zb.w * c[7];
        bar_sync_if<BAR_A, NCW * 16>(pass);
        float a0 = -Z, a1 = -Z, a2 = -Z, a3 = -Z;
        #pragma unroll
        for (int x = 0; x < NCW / 2; x++) {
            const float4 r = lds128f(red + (x * REP + wq) * (DH * 4));
            a0 = fmaf(r.x, c[x], a0); a1 = fmaf(r.y, c[x], a1); a2 = fmaf(r.z, c[x], a2); a3 = fmaf(r.w, c[x], a3);
        }
        asm volatile("" : "+f"(a0), "+f"(a1), "+f"(a2), "+f"(a3) :: "memory");
        if (w == 0) TL(8);
        bar_sync_if<BAR_O, NCW * 32>(pass);
        #pragma unroll
        for (int x = NCW / 2; x < NCW; x++) {
            const float4 r = lds128f(red + (x * REP + wq) * (DH * 4));
            a0 = fmaf(r.x, c[x], a0); a1 = fmaf(r.y, c[x], a1); a2 = fmaf(r.z, c[x], a2); a3 = fmaf(r.w, c[x], a3);
        }
        stg128_if(pass, &dst->o[sub][(lane & 15) * 4], nz(a0), nz(a1), nz(a2), nz(a3));
        if (w == 0) TL(10);
    }
}

}

extern "C" void kernel_launch(void* const* d_in, const int* in_sizes, int n_in, void* d_out, int out_size) {
    (void)in_sizes; (void)n_in; (void)out_size;
    static Scratch* scr = nullptr;
    if (!scr) {
        cudaFuncSetAttribute(kv_decode_kernel, cudaFuncAttributeMaxDynamicSharedMemorySize, SMEM_B);
        cudaGetSymbolAddress((void**)&scr, g_scratch);
    }
    kv_decode_kernel<<<NCTA, NTHREADS, SMEM_B>>>(
        (const char*)d_in[0], (const char*)d_in[1], (const char*)d_in[2], (const char*)d_in[3],
        (const char*)d_in[4], (const char*)d_in[5], (const char*)d_in[6], (__nv_bfloat16*)d_out, scr, WARM ? 0 : 1);
}
```

```cpp
#include <cuda_runtime.h>
#include <cuda_bf16.h>
#include <stdint.h>

#define PACE_X 70
#define XEND 24
#define NEND 16

namespace {

constexpr int DH        = 128;
constexpr int SKV       = 32768;
constexpr int NKVH      = 16;
constexpr int REP       = 4;
constexpr int CPH       = 4;
constexpr int NCTA      = NKVH * CPH;
constexpr int TOK       = 32;
constexpr int TPH       = SKV / TOK;
constexpr int NIT       = TPH / CPH;
constexpr int NSLOT     = 12;
constexpr int LEAD      = 8;
constexpr int TILE_B    = TOK * DH * 4;
constexpr int VP_B      = TILE_B / 4;
constexpr int VP_PITCH  = VP_B + 32;
constexpr int SLOT_B    = 4 * VP_PITCH;
constexpr int KS_B      = DH * 2;
constexpr int VS_B      = TOK * 2;
constexpr int SC_B      = 2 * KS_B + 2 * VS_B;
constexpr int Q_B       = REP * DH * 2;
constexpr int NPS       = 16;
constexpr int PS_B      = 1024 + 16;
constexpr int NVW       = 8;
constexpr int NKW       = 4;
constexpr int NTHREADS  = (1 + NVW + NKW) * 32;
static_assert(NPS >= LEAD + NSLOT / 2 + 1 && LEAD % 2 == 0 && LEAD <= NSLOT && NSLOT % NKW == 0, "bad ring shape");

__device__ __forceinline__ int slot_of_k(int n) { return (n < LEAD ? n : 2 * n - LEAD) % NSLOT; }
__device__ __forceinline__ int slot_of_v(int n) { return (n < NIT - LEAD ? 2 * n + LEAD + 1 : n + NIT) % NSLOT; }

constexpr int OFF_RING  = 0;
constexpr int OFF_SC    = OFF_RING + NSLOT * SLOT_B;
constexpr int OFF_Q     = OFF_SC + NSLOT * SC_B;
constexpr int OFF_P     = OFF_Q + Q_B;
constexpr int OFF_IO    = OFF_P + NPS * PS_B;
constexpr int OFF_IM    = OFF_IO + 2 * CPH * DH * 4;
constexpr int OFF_BK    = OFF_IM + CPH * NKW * 16;
constexpr int OFF_BV    = OFF_BK + NSLOT * 8;
constexpr int OFF_BE    = OFF_BV + NSLOT * 8;
constexpr int OFF_BP    = OFF_BE + NSLOT * 8;
constexpr int OFF_BO    = OFF_BP + NPS * 8;
constexpr int OFF_BM    = OFF_BO + 4 * 8;
constexpr int OFF_BQ    = OFF_BM + 8;
constexpr int SMEM_B    = OFF_BQ + 8;

__device__ unsigned int g_pace[32];

__device__ __forceinline__ void mbar_init(uint32_t bar, uint32_t cnt) {
    asm volatile("mbarrier.init.shared::cta.b64 [%0], %1;" :: "r"(bar), "r"(cnt) : "memory");
}
__device__ __forceinline__ void mbar_expect_tx(uint32_t bar, uint32_t bytes) {
    asm volatile("mbarrier.arrive.expect_tx.shared::cta.b64 _, [%0], %1;" :: "r"(bar), "r"(bytes) : "memory");
}
__device__ __forceinline__ void mbar_arrive_if(int on, uint32_t bar) {
    asm volatile("{ .reg .pred p; setp.ne.s32 p, %0, 0; @p mbarrier.arrive.shared::cta.b64 _, [%1]; }" :: "r"(on), "r"(bar) : "memory");
}
__device__ __forceinline__ void mbar_wait(uint32_t bar, uint32_t parity) {
    asm volatile("{\n.reg .pred p;\n.reg .u32 n;\nmov.u32 n, 0;\n"
                 "WAIT:\n"
                 "mbarrier.try_wait.parity.shared::cta.b64 p, [%0], %1;\n"
                 "@p bra.uni DONE;\n"
                 "add.u32 n, n, 1;\nsetp.lt.u32 p, n, 0x1000000;\n@p bra.uni WAIT;\ntrap;\n"
                 "DONE:\n}" :: "r"(bar), "r"(parity) : "memory");
}
__device__ __forceinline__ void bulk_g2s(uint32_t dst, const void* src, uint32_t bytes, uint32_t bar, uint64_t pol) {
    asm volatile("cp.async.bulk.shared::cluster.global.mbarrier::complete_tx::bytes.L2::cache_hint [%0], [%1], %2, [%3], %4;"
                 :: "r"(dst), "l"(src), "r"(bytes), "r"(bar), "l"(pol) : "memory");
}
__device__ __forceinline__ bool elect_one() {
    uint32_t p; asm volatile("{ .reg .pred p; elect.sync _|p, 0xffffffff; selp.u32 %0, 1, 0, p; }" : "=r"(p)); return p != 0;
}
__device__ __forceinline__ uint32_t mapa(uint32_t a, uint32_t cta) {
    uint32_t r; asm("mapa.shared::cluster.u32 %0, %1, %2;" : "=r"(r) : "r"(a), "r"(cta)); return r;
}
__device__ __forceinline__ void st_async(uint32_t dst, uint32_t bar, float x, float y, float z, float w) {
    asm volatile("st.async.shared::cluster.mbarrier::complete_tx::bytes.v4.f32 [%0], {%2,%3,%4,%5}, [%1];"
                 :: "r"(dst), "r"(bar), "f"(x), "f"(y), "f"(z), "f"(w) : "memory");
}
__device__ __forceinline__ uint32_t atom_inc(unsigned int* p, uint32_t wrap) {
    uint32_t r; asm volatile("atom.relaxed.gpu.global.inc.u32 %0, [%1], %2;" : "=r"(r) : "l"(p), "r"(wrap) : "memory"); return r;
}
__device__ __forceinline__ uint32_t ld_relaxed(const unsigned int* p) {
    uint32_t r; asm volatile("ld.relaxed.gpu.global.u32 %0, [%1];" : "=r"(r) : "l"(p) : "memory"); return r;
}
__device__ __forceinline__ int4 lds128i(uint32_t a) {
    int4 v; asm volatile("ld.shared.v4.s32 {%0,%1,%2,%3}, [%4];" : "=r"(v.x), "=r"(v.y), "=r"(v.z), "=r"(v.w) : "r"(a)); return v;
}
__device__ __forceinline__ float4 lds128f(uint32_t a) {
    float4 v; asm volatile("ld.shared.v4.f32 {%0,%1,%2,%3}, [%4];" : "=f"(v.x), "=f"(v.y), "=f"(v.z), "=f"(v.w) : "r"(a)); return v;
}
__device__ __forceinline__ uint2 lds64(uint32_t a) {
    uint2 v; asm volatile("ld.shared.v2.u32 {%0,%1}, [%2];" : "=r"(v.x), "=r"(v.y) : "r"(a)); return v;
}
__device__ __forceinline__ float lds32f(uint32_t a) {
    float v; asm volatile("ld.shared.f32 %0, [%1];" : "=f"(v) : "r"(a)); return v;
}
__device__ __forceinline__ void sts128f(uint32_t a, float x, float y, float z, float w) {
    asm volatile("st.shared.v4.f32 [%0], {%1,%2,%3,%4};" :: "r"(a), "f"(x), "f"(y), "f"(z), "f"(w) : "memory");
}
__device__ __forceinline__ void sts32f_if(int on, uint32_t a, float x) {
    asm volatile("{ .reg .pred p; setp.ne.s32 p, %0, 0; @p st.shared.f32 [%1], %2; }" :: "r"(on), "r"(a), "f"(x) : "memory");
}
__device__ __forceinline__ float bf_lo(uint32_t v) { return __uint_as_float(v << 16); }
__device__ __forceinline__ float bf_hi(uint32_t v) { return __uint_as_float(v & 0xffff0000u); }
__device__ __forceinline__ float ex2(float x) { float y; asm("ex2.approx.ftz.f32 %0, %1;" : "=f"(y) : "f"(x)); return y; }
__device__ __forceinline__ uint32_t pack_bf16(float lo, float hi) {
    uint32_t r; asm("cvt.rn.bf16x2.f32 %0, %1, %2;" : "=r"(r) : "f"(hi), "f"(lo)); return r;
}
__device__ __forceinline__ uint32_t dequant2(int a, int b, uint32_t z, uint32_t s) {
    uint32_t x = pack_bf16((float)a, (float)b);
    asm("sub.rn.bf16x2 %0, %0, %1;" : "+r"(x) : "r"(z));
    asm("mul.rn.bf16x2 %0, %0, %1;" : "+r"(x) : "r"(s));
    return x;
}
__device__ __forceinline__ void mma_bf16(float (&d)[4], uint32_t a0, uint32_t a1, uint32_t a2, uint32_t a3, uint32_t b0, uint32_t b1) {
    asm("mma.sync.aligned.m16n8k16.row.col.f32.bf16.bf16.f32 {%0,%1,%2,%3}, {%4,%5,%6,%7}, {%8,%9}, {%0,%1,%2,%3};"
        : "+f"(d[0]), "+f"(d[1]), "+f"(d[2]), "+f"(d[3]) : "r"(a0), "r"(a1), "r"(a2), "r"(a3), "r"(b0), "r"(b1));
}
__device__ __forceinline__ void mma_tf32(float (&d)[4], float a0, float a1, float a2, float a3, float b0, float b1) {
    asm("mma.sync.aligned.m16n8k8.row.col.f32.tf32.tf32.f32 {%0,%1,%2,%3}, {%4,%5,%6,%7}, {%8,%9}, {%0,%1,%2,%3};"
        : "+f"(d[0]), "+f"(d[1]), "+f"(d[2]), "+f"(d[3])
        : "r"(__float_as_uint(a0)), "r"(__float_as_uint(a1)), "r"(__float_as_uint(a2)), "r"(__float_as_uint(a3)),
          "r"(__float_as_uint(b0)), "r"(__float_as_uint(b1)));
}

__global__ void __cluster_dims__(CPH, 1, 1) __launch_bounds__(NTHREADS, 1)
kv_decode_kernel(const char* __restrict__ qk, const char* __restrict__ qv,
                 const char* __restrict__ ks, const char* __restrict__ kz,
                 const char* __restrict__ vs, const char* __restrict__ vz, const char* __restrict__ q,
                 __nv_bfloat16* __restrict__ out, unsigned int* __restrict__ pace)
{
    extern __shared__ __align__(128) char smem[];
    const int tid   = threadIdx.x;
    const int head  = blockIdx.x / CPH;
    const int rank  = blockIdx.x % CPH;
    const int tile0 = head * TPH + rank;
    if (tid < 32)
        asm volatile("cp.async.bulk.prefetch.L2.global [%0], %1;" :: "l"(qk + (size_t)tile0 * TILE_B), "n"(TILE_B) : "memory");

    const uint32_t sb = (uint32_t)__cvta_generic_to_shared(smem);
    uint64_t pol;
    asm volatile("createpolicy.fractional.L2::evict_first.b64 %0, 1.0;" : "=l"(pol));

    auto issueK = [&](int n, int slot, int b) {
        mbar_expect_tx(sb + OFF_BK + 8 * b, TILE_B + SC_B);
        bulk_g2s(sb + OFF_RING + slot * SLOT_B, qk + (size_t)(tile0 + n * CPH) * TILE_B, TILE_B, sb + OFF_BK + 8 * b, pol);
    };
    auto issueS = [&](int n, int b) {
        const uint32_t bar = sb + OFF_BK + 8 * b, sc = sb + OFF_SC + b * SC_B;
        const size_t tile = tile0 + n * CPH;
        bulk_g2s(sc,                   ks + tile * KS_B, KS_B, bar, pol);
        bulk_g2s(sc + KS_B,            kz + tile * KS_B, KS_B, bar, pol);
        bulk_g2s(sc + 2 * KS_B,        vs + tile * VS_B, VS_B, bar, pol);
        bulk_g2s(sc + 2 * KS_B + VS_B, vz + tile * VS_B, VS_B, bar, pol);
    };
    auto issueV = [&](int n, int slot, int b) {
        mbar_expect_tx(sb + OFF_BV + 8 * b, TILE_B);
        #pragma unroll
        for (int p = 0; p < 4; p++)
            bulk_g2s(sb + OFF_RING + slot * SLOT_B + p * VP_PITCH, qv + (size_t)(tile0 + n * CPH) * TILE_B + p * VP_B,
                     VP_B, sb + OFF_BV + 8 * b, pol);
    };

    constexpr int NFIRST = 4;
    if (tid < 32 && elect_one()) {
        #pragma unroll
        for (int s = 0; s < NFIRST; s++) mbar_init(sb + OFF_BK + 8 * s, 1);
        #pragma unroll
        for (int s = 0; s < NFIRST; s++) issueK(s, s, s);
        #pragma unroll
        for (int s = 0; s < NSLOT; s++) {
            if (s >= NFIRST) mbar_init(sb + OFF_BK + 8 * s, 1);
            mbar_init(sb + OFF_BV + 8 * s, 1);
            mbar_init(sb + OFF_BE + 8 * s, NVW / 2);
        }
        #pragma unroll
        for (int s = 0; s < NPS + 6; s++) mbar_init(sb + OFF_BP + 8 * s, 1);
        #pragma unroll
        for (int s = 0; s < 4; s++) mbar_expect_tx(sb + OFF_BO + 8 * s, 2 * CPH * 32 * 4);
        mbar_expect_tx(sb + OFF_BM, CPH * NKW * 16);
        asm volatile("fence.mbarrier_init.release.cluster;" ::: "memory");
    }
    __syncwarp();
    asm volatile("barrier.cluster.arrive.relaxed.aligned;" ::: "memory");
    const int lane = tid & 31;
    const int w = __shfl_sync(0xffffffffu, tid >> 5, 0);

    if (w == 0) {
        if (elect_one()) {
            mbar_expect_tx(sb + OFF_BQ, Q_B);
            bulk_g2s(sb + OFF_Q, q + (size_t)head * Q_B, Q_B, sb + OFF_BQ, pol);
            #pragma unroll 1
            for (int s = 0; s < LEAD; s++) {
                if (s >= NFIRST) issueK(s, s, s);
                issueS(s, s);
            }
            int slot = LEAD, ph = 1, nk = LEAD, bk = LEAD, nv = 0, bv = 0;
            auto next = [&](bool k) {
                mbar_wait(sb + OFF_BE + 8 * slot, ph);
                if (k) {
                    issueK(nk, slot, bk);
                    issueS(nk, bk);
                    nk++;
                    if (++bk == NSLOT) bk = 0;
                } else {
                    issueV(nv, slot, bv);
                    nv++;
                    if (++bv == NSLOT) bv = 0;
                }
                if (++slot == NSLOT) { slot = 0; ph ^= 1; }
            };
            constexpr int NSTEP = NIT - LEAD / 2;
            uint32_t pend = 0;
            int seen = 0, budget = 1 << 13;
            #pragma unroll 1
            for (int n = 0; n < NSTEP; n++) {
                const int need = n * NCTA - (n < NSTEP - NEND ? PACE_X : XEND);
                if (seen < need) {
                    seen = (int)pend;
                    while (seen < need && budget > 0) { seen = (int)ld_relaxed(pace); budget--; }
                }
                pend = atom_inc(pace, NSTEP * NCTA - 1);
                next(nk < NIT);
                next(false);
            }
        }
        __syncwarp();
        asm volatile("barrier.cluster.wait.aligned;" ::: "memory");
        return;
    }
    asm volatile("barrier.cluster.wait.aligned;" ::: "memory");
    const int g = lane >> 2, t = lane & 3;

    if (w <= NVW) {
        const int set = (w - 1) >> 2, wq = (w - 1) & 3;
        const uint32_t voff  = t * VP_PITCH + (8 * wq + g) * 16;
        const uint32_t o_dst = mapa(sb + OFF_IO + (rank * 2 + set) * (DH * 4) + (8 * wq + g) * 16, t);
        const uint32_t o_bar = mapa(sb + OFF_BO + 8 * wq, t);
        float o[4] = {0.f, 0.f, 0.f, 0.f}, M = -INFINITY;
        int sv = set, phv = 0, sp = set, php = 0;
        mbar_wait(sb + OFF_BP + 8 * sp, php);
        float4 pa = lds128f(sb + OFF_P + sp * PS_B + lane * 16);
        float4 pb = lds128f(sb + OFF_P + sp * PS_B + 512 + lane * 16);
        float  mt = lds32f(sb + OFF_P + sp * PS_B + 1024 + t * 4);
        #pragma unroll 1
        for (int it = 0; it < NIT / 2; it++) {
            const float pu[8] = {pa.x, pa.y, pa.z, pa.w, pb.x, pb.y, pb.z, pb.w};
            const float Mn = fmaxf(M, mt);
            const float alpha = ex2(M - Mn), beta = ex2(mt - Mn);
            M = Mn;
            o[0] *= alpha; o[1] *= alpha; o[2] *= alpha; o[3] *= alpha;
            if (it + 1 < NIT / 2) {
                sp += 2;
                if (sp >= NPS) { sp -= NPS; php ^= 1; }
                mbar_wait(sb + OFF_BP + 8 * sp, php);
                pa = lds128f(sb + OFF_P + sp * PS_B + lane * 16);
                pb = lds128f(sb + OFF_P + sp * PS_B + 512 + lane * 16);
                mt = lds32f(sb + OFF_P + sp * PS_B + 1024 + t * 4);
            }
            const int slot = slot_of_v(2 * it + set);
            const uint32_t vb = sb + OFF_RING + slot * SLOT_B + voff, vbar = sb + OFF_BV + 8 * sv;
            const int ph = phv;
            sv += 2;
            if (sv >= NSLOT) { sv -= NSLOT; phv ^= 1; }

            mbar_wait(vbar, ph);
            float e0[4] = {0.f, 0.f, 0.f, 0.f}, e1[4] = {0.f, 0.f, 0.f, 0.f};
            #pragma unroll
            for (int j = 0; j < 4; j++) {
                const int4 va = lds128i(vb + (2 * j) * 512), vc = lds128i(vb + (2 * j + 1) * 512);
                mma_tf32(e0, (float)va.x, (float)va.y, (float)vc.x, (float)vc.y, pu[2 * j], pu[2 * j + 1]);
                mma_tf32(e1, (float)va.z, (float)va.w, (float)vc.z, (float)vc.w, pu[2 * j], pu[2 * j + 1]);
            }
            __syncwarp();
            mbar_arrive_if(lane == 0, sb + OFF_BE + 8 * slot);
            o[0] = fmaf(e0[0] + e0[1], beta, o[0]); o[1] = fmaf(e0[2] + e0[3], beta, o[1]);
            o[2] = fmaf(e1[0] + e1[1], beta, o[2]); o[3] = fmaf(e1[2] + e1[3], beta, o[3]);
        }
        st_async(o_dst, o_bar, o[0], o[1], o[2], o[3]);
        return;
    }

    const int kw = w - NVW - 1;
    {
        const uint32_t koff = (8 * (g >> 1) + (g & 1)) * 512 + (t + 4 * (g & 1)) * 16;
        const uint32_t soff = (t + 4 * (g & 1)) * 8;
        const uint32_t keep = (g & 1) ? 0xffffffffu : 0xffffe000u, drop = (g & 1) ? 0xffffe000u : 0u;
        const float LOG2E = 1.4426950408889634f, SCALE = 0.08838834764831845f;

        uint2 qa[4][2];
        mbar_wait(sb + OFF_BQ, 0);
        #pragma unroll
        for (int c = 0; c < 4; c++) {
            qa[c][0] = lds64(sb + OFF_Q + (g >> 1) * (DH * 2) + (8 * c + t) * 8);
            qa[c][1] = lds64(sb + OFF_Q + (g >> 1) * (DH * 2) + (8 * c + t + 4) * 8);
        }
        float m = -INFINITY, mc = -INFINITY, l = 0.f, zs = 0.f;
        int sk = kw, phk = 0, sp = kw;
        #pragma unroll 1
        for (int it = kw; it < NIT; it += NKW) {
            const int slot = slot_of_k(it);
            const uint32_t kb = sb + OFF_RING + slot * SLOT_B, sc = sb + OFF_SC + sk * SC_B;
            mbar_wait(sb + OFF_BK + 8 * sk, phk);
            float d[4][4];
            #pragma unroll
            for (int j = 0; j < 4; j++) d[j][0] = d[j][1] = d[j][2] = d[j][3] = 0.f;
            #pragma unroll
            for (int c = 0; c < 4; c++) {
                #pragma unroll
                for (int u = 0; u < 2; u++) {
                    const uint2 z = lds64(sc + KS_B + (soff ^ (32 * u)) + c * 64), s = lds64(sc + (soff ^ (32 * u)) + c * 64);
                    #pragma unroll
                    for (int j = 0; j < 4; j++) {
                        const int4 k = lds128i(kb + (koff ^ (64 * u)) + j * 1024 + c * 128);
                        mma_bf16(d[j], qa[c][u].x, qa[c][u ^ 1].x, qa[c][u].y, qa[c][u ^ 1].y,
                                 dequant2(k.x, k.y, z.x, s.x), dequant2(k.z, k.w, z.y, s.y));
                    }
                }
            }
            const int4 vs8 = lds128i(sc + 2 * KS_B + t * 16), vz8 = lds128i(sc + 2 * KS_B + VS_B + t * 16);
            __syncwarp();
            mbar_arrive_if(lane < NVW / 2, sb + OFF_BE + 8 * slot);
            sk += NKW;
            if (sk >= NSLOT) { sk -= NSLOT; phk ^= 1; }

            float s[8];
            #pragma unroll
            for (int j = 0; j < 4; j++) {
                const uint32_t x = pack_bf16(d[j][0], d[j][3]);
                const uint32_t y = pack_bf16(bf_lo(x) * SCALE, bf_hi(x) * SCALE);
                s[2 * j] = bf_lo(y); s[2 * j + 1] = bf_hi(y);
            }
            float mx = fmaxf(fmaxf(fmaxf(s[0], s[1]), fmaxf(s[2], s[3])), fmaxf(fmaxf(s[4], s[5]), fmaxf(s[6], s[7])));
            if (__any_sync(0xffffffffu, mx > m)) {
                mx = fmaxf(mx, __shfl_xor_sync(0xffffffffu, mx, 1));
                mx = fmaxf(mx, __shfl_xor_sync(0xffffffffu, mx, 2));
                m = fmaxf(mx, m);
                const float mn = m * LOG2E, corr = ex2(mc - mn);
                mc = mn; l *= corr; zs *= corr;
            }
            const uint32_t vsr[4] = {(uint32_t)vs8.x, (uint32_t)vs8.y, (uint32_t)vs8.z, (uint32_t)vs8.w};
            const uint32_t vzr[4] = {(uint32_t)vz8.x, (uint32_t)vz8.y, (uint32_t)vz8.z, (uint32_t)vz8.w};
            float part[8];
            #pragma unroll
            for (int i = 0; i < 8; i++) {
                const float p  = ex2(fmaf(s[i], LOG2E, -mc));
                const float pv = p * ((i & 1) ? bf_hi(vsr[i >> 1]) : bf_lo(vsr[i >> 1]));
                l += p;
                zs = fmaf(pv, (i & 1) ? bf_hi(vzr[i >> 1]) : bf_lo(vzr[i >> 1]), zs);
                part[i] = __uint_as_float(__float_as_uint(pv) & keep) - __uint_as_float(__float_as_uint(pv) & drop);
            }
            const uint32_t pd = sb + OFF_P + sp * PS_B;
            sts128f(pd + lane * 16, part[0], part[1], part[2], part[3]);
            sts128f(pd + 512 + lane * 16, part[4], part[5], part[6], part[7]);
            sts32f_if((lane & 7) == 0, pd + 1024 + (g >> 1) * 4, mc);
            __syncwarp();
            mbar_arrive_if(lane == 0, sb + OFF_BP + 8 * sp);
            sp += NKW;
            if (sp >= NPS) sp -= NPS;
        }
        l  += __shfl_xor_sync(0xffffffffu, l, 1);
        zs += __shfl_xor_sync(0xffffffffu, zs, 1);
        l  += __shfl_xor_sync(0xffffffffu, l, 2);
        zs += __shfl_xor_sync(0xffffffffu, zs, 2);
        if ((lane & 7) == 0)
            st_async(mapa(sb + OFF_IM + (rank * NKW + kw) * 16, g >> 1), mapa(sb + OFF_BM, g >> 1), mc, l, zs, 0.f);
        __syncwarp();
    }

    mbar_wait(sb + OFF_BM, 0);
    const float4 ml = lds128f(sb + OFF_IM + (lane & 15) * 16);
    const float mv = fmaxf(ml.x, __shfl_xor_sync(0xffffffffu, ml.x, 2));
    float M = fmaxf(mv, __shfl_xor_sync(0xffffffffu, mv, 1));
    M = fmaxf(M, __shfl_xor_sync(0xffffffffu, M, 4));
    M = fmaxf(M, __shfl_xor_sync(0xffffffffu, M, 8));
    const float cw = ex2(ml.x - M);
    float L = ml.y * cw, Z = ml.z * cw;
    #pragma unroll
    for (int x = 1; x <= 8; x <<= 1) {
        L += __shfl_xor_sync(0xffffffffu, L, x);
        Z += __shfl_xor_sync(0xffffffffu, Z, x);
    }
    const float inv = 1.f / L, cv = ex2(mv - M) * inv;
    float c[2 * CPH];
    #pragma unroll
    for (int x = 0; x < 2 * CPH; x++) c[x] = __shfl_sync(0xffffffffu, cv, (x >> 1) * NKW + (x & 1));
    float a = -Z * inv, b = 0.f;
    const uint32_t src = __shfl_sync(0xffffffffu, sb + OFF_IO + (32 * kw + lane) * 4, lane);
    __nv_bfloat16* dst = (__nv_bfloat16*)__shfl_sync(0xffffffffu, (unsigned long long)(out + blockIdx.x * DH + 32 * kw + lane), lane);
    mbar_wait(sb + OFF_BO + 8 * kw, 0);
    #pragma unroll
    for (int x = 0; x < 2 * CPH; x += 2) {
        a = fmaf(lds32f(src + x * (DH * 4)), c[x], a);
        b = fmaf(lds32f(src + (x + 1) * (DH * 4)), c[x + 1], b);
    }
    __stcg(dst, __float2bfloat16_rn(a + b));
}

}

extern "C" void kernel_launch(void* const* d_in, const int* in_sizes, int n_in, void* d_out, int out_size) {
    (void)in_sizes; (void)n_in; (void)out_size;
    static unsigned int* pace = nullptr;
    if (!pace) {
        cudaFuncSetAttribute(kv_decode_kernel, cudaFuncAttributeMaxDynamicSharedMemorySize, SMEM_B);
        cudaGetSymbolAddress((void**)&pace, g_pace);
    }
    kv_decode_kernel<<<NCTA, NTHREADS, SMEM_B>>>(
        (const char*)d_in[1], (const char*)d_in[2], (const char*)d_in[3], (const char*)d_in[4],
        (const char*)d_in[5], (const char*)d_in[6], (const char*)d_in[0], (__nv_bfloat16*)d_out, pace
        );
}
```

```cpp
#include <cuda_runtime.h>
#include <cuda_bf16.h>
#include <stdint.h>

namespace {

constexpr int DH        = 128;
constexpr int SKV       = 32768;
constexpr int NKVH      = 16;
constexpr int REP       = 4;
constexpr int CPH       = 4;
constexpr int NCTA      = NKVH * CPH;
constexpr int TOK       = 32;
constexpr int TPH       = SKV / TOK;
constexpr int NIT       = TPH / CPH;
constexpr int NSLOT     = 12;
constexpr int LEAD      = 8;
constexpr int TILE_B    = TOK * DH * 4;
constexpr int VP_B      = TILE_B / 4;
constexpr int VP_PITCH  = VP_B + 32;
constexpr int SLOT_B    = 4 * VP_PITCH;
constexpr int KS_B      = DH * 2;
constexpr int VS_B      = TOK * 2;
constexpr int SC_B      = 2 * KS_B + 2 * VS_B;
constexpr int Q_B       = REP * DH * 2;
constexpr int NPS       = 16;
constexpr int PS_B      = 1024 + 16;
constexpr int NVW       = 8;
constexpr int NKW       = 4;
constexpr int NTHREADS  = (1 + NVW + NKW) * 32;
constexpr int SLACK     = 64;
constexpr int SLACK_END = 32;
constexpr int NEND      = 12;
static_assert(NPS >= LEAD + NSLOT / 2 + 1 && LEAD % 2 == 0 && LEAD <= NSLOT && NSLOT % NKW == 0, "bad ring shape");

__device__ __forceinline__ int slot_of_k(int n) { return (n < LEAD ? n : 2 * n - LEAD) % NSLOT; }
__device__ __forceinline__ int slot_of_v(int n) { return (n < NIT - LEAD ? 2 * n + LEAD + 1 : n + NIT) % NSLOT; }

constexpr int OFF_RING  = 0;
constexpr int OFF_SC    = OFF_RING + NSLOT * SLOT_B;
constexpr int OFF_Q     = OFF_SC + NSLOT * SC_B;
constexpr int OFF_P     = OFF_Q + Q_B;
constexpr int OFF_IO    = OFF_P + NPS * PS_B;
constexpr int OFF_IM    = OFF_IO + 2 * CPH * DH * 4;
constexpr int OFF_BK    = OFF_IM + CPH * NKW * 16;
constexpr int OFF_BV    = OFF_BK + NSLOT * 8;
constexpr int OFF_BE    = OFF_BV + NSLOT * 8;
constexpr int OFF_BP    = OFF_BE + NSLOT * 8;
constexpr int OFF_BO    = OFF_BP + NPS * 8;
constexpr int OFF_BM    = OFF_BO + 4 * 8;
constexpr int OFF_BQ    = OFF_BM + 8;
constexpr int SMEM_B    = OFF_BQ + 8;

__device__ unsigned int g_pace[32];

__device__ __forceinline__ void mbar_init(uint32_t bar, uint32_t cnt) {
    asm volatile("mbarrier.init.shared::cta.b64 [%0], %1;" :: "r"(bar), "r"(cnt) : "memory");
}
__device__ __forceinline__ void mbar_expect_tx(uint32_t bar, uint32_t bytes) {
    asm volatile("mbarrier.arrive.expect_tx.shared::cta.b64 _, [%0], %1;" :: "r"(bar), "r"(bytes) : "memory");
}
__device__ __forceinline__ void mbar_arrive_if(int on, uint32_t bar) {
    asm volatile("{ .reg .pred p; setp.ne.s32 p, %0, 0; @p mbarrier.arrive.shared::cta.b64 _, [%1]; }" :: "r"(on), "r"(bar) : "memory");
}
__device__ __forceinline__ void mbar_wait(uint32_t bar, uint32_t parity) {
    asm volatile("{\n.reg .pred p;\n.reg .u32 n;\nmov.u32 n, 0;\n"
                 "WAIT:\n"
                 "mbarrier.try_wait.parity.shared::cta.b64 p, [%0], %1;\n"
                 "@p bra.uni DONE;\n"
                 "add.u32 n, n, 1;\nsetp.lt.u32 p, n, 0x400000;\n@p bra.uni WAIT;\ntrap;\n"
                 "DONE:\n}" :: "r"(bar), "r"(parity) : "memory");
}
__device__ __forceinline__ void mbar_wait_cluster(uint32_t bar, uint32_t parity) {
    asm volatile("{\n.reg .pred p;\n.reg .u32 n;\nmov.u32 n, 0;\n"
                 "WAIT:\n"
                 "mbarrier.try_wait.parity.acquire.cluster.shared::cta.b64 p, [%0], %1;\n"
                 "@p bra.uni DONE;\n"
                 "add.u32 n, n, 1;\nsetp.lt.u32 p, n, 0x400000;\n@p bra.uni WAIT;\ntrap;\n"
                 "DONE:\n}" :: "r"(bar), "r"(parity) : "memory");
}
__device__ __forceinline__ void bulk_g2s(uint32_t dst, const void* src, uint32_t bytes, uint32_t bar, uint64_t pol) {
    asm volatile("cp.async.bulk.shared::cluster.global.mbarrier::complete_tx::bytes.L2::cache_hint [%0], [%1], %2, [%3], %4;"
                 :: "r"(dst), "l"(src), "r"(bytes), "r"(bar), "l"(pol) : "memory");
}
__device__ __forceinline__ bool elect_one() {
    uint32_t p; asm volatile("{ .reg .pred p; elect.sync _|p, 0xffffffff; selp.u32 %0, 1, 0, p; }" : "=r"(p)); return p != 0;
}
__device__ __forceinline__ uint32_t mapa(uint32_t a, uint32_t cta) {
    uint32_t r; asm("mapa.shared::cluster.u32 %0, %1, %2;" : "=r"(r) : "r"(a), "r"(cta)); return r;
}
__device__ __forceinline__ void st_async(uint32_t dst, uint32_t bar, float x, float y, float z, float w) {
    asm volatile("st.async.shared::cluster.mbarrier::complete_tx::bytes.v4.f32 [%0], {%2,%3,%4,%5}, [%1];"
                 :: "r"(dst), "r"(bar), "f"(x), "f"(y), "f"(z), "f"(w) : "memory");
}
__device__ __forceinline__ uint32_t atom_inc(unsigned int* p, uint32_t wrap) {
    uint32_t r; asm volatile("atom.relaxed.gpu.global.inc.u32 %0, [%1], %2;" : "=r"(r) : "l"(p), "r"(wrap) : "memory"); return r;
}
__device__ __forceinline__ uint32_t ld_relaxed(const unsigned int* p) {
    uint32_t r; asm volatile("ld.relaxed.gpu.global.u32 %0, [%1];" : "=r"(r) : "l"(p) : "memory"); return r;
}
__device__ __forceinline__ int4 lds128i(uint32_t a) {
    int4 v; asm volatile("ld.shared.v4.s32 {%0,%1,%2,%3}, [%4];" : "=r"(v.x), "=r"(v.y), "=r"(v.z), "=r"(v.w) : "r"(a)); return v;
}
__device__ __forceinline__ float4 lds128f(uint32_t a) {
    float4 v; asm volatile("ld.shared.v4.f32 {%0,%1,%2,%3}, [%4];" : "=f"(v.x), "=f"(v.y), "=f"(v.z), "=f"(v.w) : "r"(a)); return v;
}
__device__ __forceinline__ uint2 lds64(uint32_t a) {
    uint2 v; asm volatile("ld.shared.v2.u32 {%0,%1}, [%2];" : "=r"(v.x), "=r"(v.y) : "r"(a)); return v;
}
__device__ __forceinline__ float lds32f(uint32_t a) {
    float v; asm volatile("ld.shared.f32 %0, [%1];" : "=f"(v) : "r"(a)); return v;
}
__device__ __forceinline__ void sts128f(uint32_t a, float x, float y, float z, float w) {
    asm volatile("st.shared.v4.f32 [%0], {%1,%2,%3,%4};" :: "r"(a), "f"(x), "f"(y), "f"(z), "f"(w) : "memory");
}
__device__ __forceinline__ void sts32f_if(int on, uint32_t a, float x) {
    asm volatile("{ .reg .pred p; setp.ne.s32 p, %0, 0; @p st.shared.f32 [%1], %2; }" :: "r"(on), "r"(a), "f"(x) : "memory");
}
__device__ __forceinline__ float bf_lo(uint32_t v) { return __uint_as_float(v << 16); }
__device__ __forceinline__ float bf_hi(uint32_t v) { return __uint_as_float(v & 0xffff0000u); }
__device__ __forceinline__ float ex2(float x) { float y; asm("ex2.approx.ftz.f32 %0, %1;" : "=f"(y) : "f"(x)); return y; }
__device__ __forceinline__ uint32_t pack_bf16(float lo, float hi) {
    uint32_t r; asm("cvt.rn.bf16x2.f32 %0, %1, %2;" : "=r"(r) : "f"(hi), "f"(lo)); return r;
}
__device__ __forceinline__ uint32_t dequant2(int a, int b, uint32_t z, uint32_t s) {
    uint32_t x = pack_bf16((float)a, (float)b);
    asm("sub.rn.bf16x2 %0, %0, %1;" : "+r"(x) : "r"(z));
    asm("mul.rn.bf16x2 %0, %0, %1;" : "+r"(x) : "r"(s));
    return x;
}
__device__ __forceinline__ void mma_bf16(float (&d)[4], uint32_t a0, uint32_t a1, uint32_t a2, uint32_t a3, uint32_t b0, uint32_t b1) {
    asm("mma.sync.aligned.m16n8k16.row.col.f32.bf16.bf16.f32 {%0,%1,%2,%3}, {%4,%5,%6,%7}, {%8,%9}, {%0,%1,%2,%3};"
        : "+f"(d[0]), "+f"(d[1]), "+f"(d[2]), "+f"(d[3]) : "r"(a0), "r"(a1), "r"(a2), "r"(a3), "r"(b0), "r"(b1));
}
__device__ __forceinline__ void mma_tf32(float (&d)[4], float a0, float a1, float a2, float a3, float b0, float b1) {
    asm("mma.sync.aligned.m16n8k8.row.col.f32.tf32.tf32.f32 {%0,%1,%2,%3}, {%4,%5,%6,%7}, {%8,%9}, {%0,%1,%2,%3};"
        : "+f"(d[0]), "+f"(d[1]), "+f"(d[2]), "+f"(d[3])
        : "r"(__float_as_uint(a0)), "r"(__float_as_uint(a1)), "r"(__float_as_uint(a2)), "r"(__float_as_uint(a3)),
          "r"(__float_as_uint(b0)), "r"(__float_as_uint(b1)));
}

__global__ void __cluster_dims__(CPH, 1, 1) __launch_bounds__(NTHREADS, 1)
kv_decode_kernel(const char* __restrict__ qk, const char* __restrict__ qv,
                 const char* __restrict__ ks, const char* __restrict__ kz,
                 const char* __restrict__ vs, const char* __restrict__ vz, const char* __restrict__ q,
                 __nv_bfloat16* __restrict__ out, unsigned int* __restrict__ pace)
{
    extern __shared__ __align__(128) char smem[];
    const int tid   = threadIdx.x;
    const int head  = blockIdx.x / CPH;
    const int rank  = blockIdx.x % CPH;
    const int tile0 = head * TPH + rank;
    if (tid < 32)
        asm volatile("cp.async.bulk.prefetch.L2.global [%0], %1;" :: "l"(qk + (size_t)tile0 * TILE_B), "n"(TILE_B) : "memory");

    const uint32_t sb = (uint32_t)__cvta_generic_to_shared(smem);
    uint64_t pol;
    asm volatile("createpolicy.fractional.L2::evict_first.b64 %0, 1.0;" : "=l"(pol));

    auto issueK = [&](int n, int slot, int b) {
        mbar_expect_tx(sb + OFF_BK + 8 * b, TILE_B + SC_B);
        bulk_g2s(sb + OFF_RING + slot * SLOT_B, qk + (size_t)(tile0 + n * CPH) * TILE_B, TILE_B, sb + OFF_BK + 8 * b, pol);
    };
    auto issueS = [&](int n, int b) {
        const uint32_t bar = sb + OFF_BK + 8 * b, sc = sb + OFF_SC + b * SC_B;
        const size_t tile = tile0 + n * CPH;
        bulk_g2s(sc,                   ks + tile * KS_B, KS_B, bar, pol);
        bulk_g2s(sc + KS_B,            kz + tile * KS_B, KS_B, bar, pol);
        bulk_g2s(sc + 2 * KS_B,        vs + tile * VS_B, VS_B, bar, pol);
        bulk_g2s(sc + 2 * KS_B + VS_B, vz + tile * VS_B, VS_B, bar, pol);
    };
    auto issueV = [&](int n, int slot, int b) {
        mbar_expect_tx(sb + OFF_BV + 8 * b, TILE_B);
        #pragma unroll
        for (int p = 0; p < 4; p++)
            bulk_g2s(sb + OFF_RING + slot * SLOT_B + p * VP_PITCH, qv + (size_t)(tile0 + n * CPH) * TILE_B + p * VP_B,
                     VP_B, sb + OFF_BV + 8 * b, pol);
    };

    constexpr int NFIRST = 4;
    if (tid < 32 && elect_one()) {
        #pragma unroll
        for (int s = 0; s < NFIRST; s++) mbar_init(sb + OFF_BK + 8 * s, 1);
        #pragma unroll
        for (int s = 0; s < NFIRST; s++) issueK(s, s, s);
        #pragma unroll
        for (int s = 0; s < NSLOT; s++) {
            if (s >= NFIRST) mbar_init(sb + OFF_BK + 8 * s, 1);
            mbar_init(sb + OFF_BV + 8 * s, 1);
            mbar_init(sb + OFF_BE + 8 * s, NVW / 2);
        }
        #pragma unroll
        for (int s = 0; s < NPS + 6; s++) mbar_init(sb + OFF_BP + 8 * s, 1);
        #pragma unroll
        for (int s = 0; s < 4; s++) mbar_expect_tx(sb + OFF_BO + 8 * s, 2 * CPH * 32 * 4);
        mbar_expect_tx(sb + OFF_BM, CPH * NKW * 16);
        asm volatile("fence.mbarrier_init.release.cluster;" ::: "memory");
    }
    __syncwarp();
    asm volatile("barrier.cluster.arrive.relaxed.aligned;" ::: "memory");
    const int lane = tid & 31;
    const int w = __shfl_sync(0xffffffffu, tid >> 5, 0);

    if (w == 0) {
        if (elect_one()) {
            mbar_expect_tx(sb + OFF_BQ, Q_B);
            bulk_g2s(sb + OFF_Q, q + (size_t)head * Q_B, Q_B, sb + OFF_BQ, pol);
            #pragma unroll 1
            for (int s = 0; s < LEAD; s++) {
                if (s >= NFIRST) issueK(s, s, s);
                issueS(s, s);
            }
            int slot = LEAD, ph = 1, nk = LEAD, bk = LEAD, nv = 0, bv = 0;
            auto next = [&](bool k) {
                mbar_wait(sb + OFF_BE + 8 * slot, ph);
                if (k) {
                    issueK(nk, slot, bk);
                    issueS(nk, bk);
                    nk++;
                    if (++bk == NSLOT) bk = 0;
                } else {
                    issueV(nv, slot, bv);
                    nv++;
                    if (++bv == NSLOT) bv = 0;
                }
                if (++slot == NSLOT) { slot = 0; ph ^= 1; }
            };
            constexpr int NSTEP = NIT - LEAD / 2;
            uint32_t pend = 0;
            int seen = 0, budget = 1 << 13;
            #pragma unroll 1
            for (int n = 0; n < NSTEP; n++) {
                const int need = n * NCTA - (n < NSTEP - NEND ? SLACK : SLACK_END);
                if (seen < need) {
                    seen = (int)pend;
                    while (seen < need && budget > 0) { seen = (int)ld_relaxed(pace); budget--; }
                }
                pend = atom_inc(pace, NSTEP * NCTA - 1);
                next(nk < NIT);
                next(false);
            }
        }
        __syncwarp();
        asm volatile("barrier.cluster.wait.aligned;" ::: "memory");
        return;
    }
    asm volatile("barrier.cluster.wait.aligned;" ::: "memory");
    const int g = lane >> 2, t = lane & 3;

    if (w <= NVW) {
        const int set = (w - 1) >> 2, wq = (w - 1) & 3;
        const uint32_t voff  = t * VP_PITCH + (8 * wq + g) * 16;
        const uint32_t o_dst = mapa(sb + OFF_IO + (rank * 2 + set) * (DH * 4) + (8 * wq + g) * 16, t);
        const uint32_t o_bar = mapa(sb + OFF_BO + 8 * wq, t);
        float o[4] = {0.f, 0.f, 0.f, 0.f}, M = -INFINITY;
        int sv = set, phv = 0, sp = set, php = 0;
        mbar_wait(sb + OFF_BP + 8 * sp, php);
        float4 pa = lds128f(sb + OFF_P + sp * PS_B + lane * 16);
        float4 pb = lds128f(sb + OFF_P + sp * PS_B + 512 + lane * 16);
        float  mt = lds32f(sb + OFF_P + sp * PS_B + 1024 + t * 4);
        #pragma unroll 1
        for (int it = 0; it < NIT / 2; it++) {
            const float pu[8] = {pa.x, pa.y, pa.z, pa.w, pb.x, pb.y, pb.z, pb.w};
            const float Mn = fmaxf(M, mt);
            const float alpha = ex2(M - Mn), beta = ex2(mt - Mn);
            M = Mn;
            o[0] *= alpha; o[1] *= alpha; o[2] *= alpha; o[3] *= alpha;
            if (it + 1 < NIT / 2) {
                sp += 2;
                if (sp >= NPS) { sp -= NPS; php ^= 1; }
                mbar_wait(sb + OFF_BP + 8 * sp, php);
                pa = lds128f(sb + OFF_P + sp * PS_B + lane * 16);
                pb = lds128f(sb + OFF_P + sp * PS_B + 512 + lane * 16);
                mt = lds32f(sb + OFF_P + sp * PS_B + 1024 + t * 4);
            }
            const int slot = slot_of_v(2 * it + set);
            const uint32_t vb = sb + OFF_RING + slot * SLOT_B + voff, vbar = sb + OFF_BV + 8 * sv;
            const int ph = phv;
            sv += 2;
            if (sv >= NSLOT) { sv -= NSLOT; phv ^= 1; }

            mbar_wait(vbar, ph);
            float e0[4] = {0.f, 0.f, 0.f, 0.f}, e1[4] = {0.f, 0.f, 0.f, 0.f};
            #pragma unroll
            for (int j = 0; j < 4; j++) {
                const int4 va = lds128i(vb + (2 * j) * 512), vc = lds128i(vb + (2 * j + 1) * 512);
                mma_tf32(e0, (float)va.x, (float)va.y, (float)vc.x, (float)vc.y, pu[2 * j], pu[2 * j + 1]);
                mma_tf32(e1, (float)va.z, (float)va.w, (float)vc.z, (float)vc.w, pu[2 * j], pu[2 * j + 1]);
            }
            __syncwarp();
            mbar_arrive_if(lane == 0, sb + OFF_BE + 8 * slot);
            o[0] = fmaf(e0[0] + e0[1], beta, o[0]); o[1] = fmaf(e0[2] + e0[3], beta, o[1]);
            o[2] = fmaf(e1[0] + e1[1], beta, o[2]); o[3] = fmaf(e1[2] + e1[3], beta, o[3]);
        }
        st_async(o_dst, o_bar, o[0], o[1], o[2], o[3]);
        return;
    }

    const int kw = w - NVW - 1;
    {
        const uint32_t koff = (8 * (g >> 1) + (g & 1)) * 512 + (t + 4 * (g & 1)) * 16;
        const uint32_t soff = (t + 4 * (g & 1)) * 8;
        const uint32_t keep = (g & 1) ? 0xffffffffu : 0xffffe000u, drop = (g & 1) ? 0xffffe000u : 0u;
        const float LOG2E = 1.4426950408889634f, SCALE = 0.08838834764831845f;

        uint2 qa[4][2];
        mbar_wait(sb + OFF_BQ, 0);
        #pragma unroll
        for (int c = 0; c < 4; c++) {
            qa[c][0] = lds64(sb + OFF_Q + (g >> 1) * (DH * 2) + (8 * c + t) * 8);
            qa[c][1] = lds64(sb + OFF_Q + (g >> 1) * (DH * 2) + (8 * c + t + 4) * 8);
        }
        float m = -INFINITY, mc = -INFINITY, l = 0.f, zs = 0.f;
        int sk = kw, phk = 0, sp = kw;
        #pragma unroll 1
        for (int it = kw; it < NIT; it += NKW) {
            const int slot = slot_of_k(it);
            const uint32_t kb = sb + OFF_RING + slot * SLOT_B, sc = sb + OFF_SC + sk * SC_B;
            mbar_wait(sb + OFF_BK + 8 * sk, phk);
            float d[4][4];
            #pragma unroll
            for (int j = 0; j < 4; j++) d[j][0] = d[j][1] = d[j][2] = d[j][3] = 0.f;
            #pragma unroll
            for (int c = 0; c < 4; c++) {
                #pragma unroll
                for (int u = 0; u < 2; u++) {
                    const uint2 z = lds64(sc + KS_B + (soff ^ (32 * u)) + c * 64), s = lds64(sc + (soff ^ (32 * u)) + c * 64);
                    #pragma unroll
                    for (int j = 0; j < 4; j++) {
                        const int4 k = lds128i(kb + (koff ^ (64 * u)) + j * 1024 + c * 128);
                        mma_bf16(d[j], qa[c][u].x, qa[c][u ^ 1].x, qa[c][u].y, qa[c][u ^ 1].y,
                                 dequant2(k.x, k.y, z.x, s.x), dequant2(k.z, k.w, z.y, s.y));
                    }
                }
            }
            const int4 vs8 = lds128i(sc + 2 * KS_B + t * 16), vz8 = lds128i(sc + 2 * KS_B + VS_B + t * 16);
            __syncwarp();
            mbar_arrive_if(lane < NVW / 2, sb + OFF_BE + 8 * slot);
            sk += NKW;
            if (sk >= NSLOT) { sk -= NSLOT; phk ^= 1; }

            float s[8];
            #pragma unroll
            for (int j = 0; j < 4; j++) {
                const uint32_t x = pack_bf16(d[j][0], d[j][3]);
                const uint32_t y = pack_bf16(bf_lo(x) * SCALE, bf_hi(x) * SCALE);
                s[2 * j] = bf_lo(y); s[2 * j + 1] = bf_hi(y);
            }
            float mx = fmaxf(fmaxf(fmaxf(s[0], s[1]), fmaxf(s[2], s[3])), fmaxf(fmaxf(s[4], s[5]), fmaxf(s[6], s[7])));
            if (__any_sync(0xffffffffu, mx > m)) {
                mx = fmaxf(mx, __shfl_xor_sync(0xffffffffu, mx, 1));
                mx = fmaxf(mx, __shfl_xor_sync(0xffffffffu, mx, 2));
                m = fmaxf(mx, m);
                const float mn = m * LOG2E, corr = ex2(mc - mn);
                mc = mn; l *= corr; zs *= corr;
            }
            const uint32_t vsr[4] = {(uint32_t)vs8.x, (uint32_t)vs8.y, (uint32_t)vs8.z, (uint32_t)vs8.w};
            const uint32_t vzr[4] = {(uint32_t)vz8.x, (uint32_t)vz8.y, (uint32_t)vz8.z, (uint32_t)vz8.w};
            float part[8];
            #pragma unroll
            for (int i = 0; i < 8; i++) {
                const float p  = ex2(fmaf(s[i], LOG2E, -mc));
                const float pv = p * ((i & 1) ? bf_hi(vsr[i >> 1]) : bf_lo(vsr[i >> 1]));
                l += p;
                zs = fmaf(pv, (i & 1) ? bf_hi(vzr[i >> 1]) : bf_lo(vzr[i >> 1]), zs);
                part[i] = __uint_as_float(__float_as_uint(pv) & keep) - __uint_as_float(__float_as_uint(pv) & drop);
            }
            const uint32_t pd = sb + OFF_P + sp * PS_B;
            sts128f(pd + lane * 16, part[0], part[1], part[2], part[3]);
            sts128f(pd + 512 + lane * 16, part[4], part[5], part[6], part[7]);
            sts32f_if((lane & 7) == 0, pd + 1024 + (g >> 1) * 4, mc);
            __syncwarp();
            mbar_arrive_if(lane == 0, sb + OFF_BP + 8 * sp);
            sp += NKW;
            if (sp >= NPS) sp -= NPS;
        }
        l  += __shfl_xor_sync(0xffffffffu, l, 1);
        zs += __shfl_xor_sync(0xffffffffu, zs, 1);
        l  += __shfl_xor_sync(0xffffffffu, l, 2);
        zs += __shfl_xor_sync(0xffffffffu, zs, 2);
        if ((lane & 7) == 0)
            st_async(mapa(sb + OFF_IM + (rank * NKW + kw) * 16, g >> 1), mapa(sb + OFF_BM, g >> 1), mc, l, zs, 0.f);
        __syncwarp();
    }

    mbar_wait_cluster(sb + OFF_BM, 0);
    const float4 ml = lds128f(sb + OFF_IM + (lane & 15) * 16);
    const float mv = fmaxf(ml.x, __shfl_xor_sync(0xffffffffu, ml.x, 2));
    float M = fmaxf(mv, __shfl_xor_sync(0xffffffffu, mv, 1));
    M = fmaxf(M, __shfl_xor_sync(0xffffffffu, M, 4));
    M = fmaxf(M, __shfl_xor_sync(0xffffffffu, M, 8));
    const float cw = ex2(ml.x - M);
    float L = ml.y * cw, Z = ml.z * cw;
    #pragma unroll
    for (int x = 1; x <= 8; x <<= 1) {
        L += __shfl_xor_sync(0xffffffffu, L, x);
        Z += __shfl_xor_sync(0xffffffffu, Z, x);
    }
    const float inv = 1.f / L, cv = ex2(mv - M) * inv;
    float c[2 * CPH];
    #pragma unroll
    for (int x = 0; x < 2 * CPH; x++) c[x] = __shfl_sync(0xffffffffu, cv, (x >> 1) * NKW + (x & 1));
    float a = -Z * inv, b = 0.f;
    const uint32_t src = __shfl_sync(0xffffffffu, sb + OFF_IO + (32 * kw + lane) * 4, lane);
    __nv_bfloat16* dst = (__nv_bfloat16*)__shfl_sync(0xffffffffu, (unsigned long long)(out + blockIdx.x * DH + 32 * kw + lane), lane);
    mbar_wait_cluster(sb + OFF_BO + 8 * kw, 0);
    #pragma unroll
    for (int x = 0; x < 2 * CPH; x += 2) {
        a = fmaf(lds32f(src + x * (DH * 4)), c[x], a);
        b = fmaf(lds32f(src + (x + 1) * (DH * 4)), c[x + 1], b);
    }
    __stcg(dst, __float2bfloat16_rn(a + b));
}

}

extern "C" void kernel_launch(void* const* d_in, const int* in_sizes, int n_in, void* d_out, int out_size) {
    (void)in_sizes; (void)n_in; (void)out_size;
    static unsigned int* pace = nullptr;
    if (!pace) {
        cudaFuncSetAttribute(kv_decode_kernel, cudaFuncAttributeMaxDynamicSharedMemorySize, SMEM_B);
        cudaGetSymbolAddress((void**)&pace, g_pace);
    }
    kv_decode_kernel<<<NCTA, NTHREADS, SMEM_B>>>(
        (const char*)d_in[1], (const char*)d_in[2], (const char*)d_in[3], (const char*)d_in[4],
        (const char*)d_in[5], (const char*)d_in[6], (const char*)d_in[0], (__nv_bfloat16*)d_out, pace);
}
```

```cpp
#include <cuda_runtime.h>
#include <cuda_bf16.h>
#include <float.h>
#include <stdint.h>

namespace {

constexpr int DH        = 128;
constexpr int SKV       = 32768;
constexpr int NKVH      = 16;
constexpr int REP       = 4;
constexpr int CPH       = 4;
constexpr int NCTA      = NKVH * CPH;
constexpr int TOK       = 32;
constexpr int TPH       = SKV / TOK;
constexpr int NIT       = TPH / CPH;
constexpr int NSLOT     = 12;
constexpr int LEAD      = 8;
constexpr int TILE_B    = TOK * DH * 4;
constexpr int VP_B      = TILE_B / 4;
constexpr int VP_PITCH  = VP_B + 32;
constexpr int SLOT_B    = 4 * VP_PITCH;
constexpr int KS_B      = DH * 2;
constexpr int VS_B      = TOK * 2;
constexpr int SC_B      = 2 * KS_B + 2 * VS_B;
constexpr int Q_B       = REP * DH * 2;
constexpr int NPS       = 16;
constexpr int PS_B      = 1024 + 16;
constexpr int NVW       = 8;
constexpr int NKW       = 4;
constexpr int NTHREADS  = (1 + NVW + NKW) * 32;
constexpr int SLACK     = 56;
constexpr int SLACK_END = 32;
constexpr int NEND      = 12;
static_assert(NPS >= LEAD + NSLOT / 2 + 1 && LEAD % 2 == 0 && LEAD <= NSLOT && NSLOT % NKW == 0, "bad ring shape");

__device__ __forceinline__ int slot_of_k(int n) { return (n < LEAD ? n : 2 * n - LEAD) % NSLOT; }
__device__ __forceinline__ int slot_of_v(int n) { return (n < NIT - LEAD ? 2 * n + LEAD + 1 : n + NIT) % NSLOT; }

constexpr int OFF_RING  = 0;
constexpr int OFF_SC    = OFF_RING + NSLOT * SLOT_B;
constexpr int OFF_Q     = OFF_SC + NSLOT * SC_B;
constexpr int OFF_P     = OFF_Q + Q_B;
constexpr int OFF_IO    = OFF_P + NPS * PS_B;
constexpr int OFF_IM    = OFF_IO + 2 * CPH * DH * 4;
constexpr int OFF_BK    = OFF_IM + CPH * NKW * 16;
constexpr int OFF_BV    = OFF_BK + NSLOT * 8;
constexpr int OFF_BE    = OFF_BV + NSLOT * 8;
constexpr int OFF_BP    = OFF_BE + NSLOT * 8;
constexpr int OFF_BO    = OFF_BP + NPS * 8;
constexpr int OFF_BM    = OFF_BO + 4 * 8;
constexpr int OFF_BQ    = OFF_BM + 8;
constexpr int SMEM_B    = OFF_BQ + 8;

__device__ unsigned int g_pace[32];

__device__ __forceinline__ void mbar_init(uint32_t bar, uint32_t cnt) {
    asm volatile("mbarrier.init.shared::cta.b64 [%0], %1;" :: "r"(bar), "r"(cnt) : "memory");
}
__device__ __forceinline__ void mbar_expect_tx(uint32_t bar, uint32_t bytes) {
    asm volatile("mbarrier.arrive.expect_tx.shared::cta.b64 _, [%0], %1;" :: "r"(bar), "r"(bytes) : "memory");
}
__device__ __forceinline__ void mbar_arrive_if(int on, uint32_t bar) {
    asm volatile("{ .reg .pred p; setp.ne.s32 p, %0, 0; @p mbarrier.arrive.shared::cta.b64 _, [%1]; }" :: "r"(on), "r"(bar) : "memory");
}
__device__ __forceinline__ void mbar_wait(uint32_t bar, uint32_t parity) {
    asm volatile("{\n.reg .pred p;\n.reg .u32 n;\nmov.u32 n, 0;\n"
                 "WAIT:\n"
                 "mbarrier.try_wait.parity.shared::cta.b64 p, [%0], %1;\n"
                 "@p bra.uni DONE;\n"
                 "add.u32 n, n, 1;\nsetp.lt.u32 p, n, 0x100000;\n@p bra.uni WAIT;\ntrap;\n"
                 "DONE:\n}" :: "r"(bar), "r"(parity) : "memory");
}
__device__ __forceinline__ void mbar_wait_cluster(uint32_t bar, uint32_t parity) {
    asm volatile("{\n.reg .pred p;\n.reg .u32 n;\nmov.u32 n, 0;\n"
                 "WAIT:\n"
                 "mbarrier.try_wait.parity.acquire.cluster.shared::cta.b64 p, [%0], %1;\n"
                 "@p bra.uni DONE;\n"
                 "add.u32 n, n, 1;\nsetp.lt.u32 p, n, 0x100000;\n@p bra.uni WAIT;\ntrap;\n"
                 "DONE:\n}" :: "r"(bar), "r"(parity) : "memory");
}
__device__ __forceinline__ void bulk_g2s(uint32_t dst, const void* src, uint32_t bytes, uint32_t bar, uint64_t pol) {
    asm volatile("cp.async.bulk.shared::cluster.global.mbarrier::complete_tx::bytes.L2::cache_hint [%0], [%1], %2, [%3], %4;"
                 :: "r"(dst), "l"(src), "r"(bytes), "r"(bar), "l"(pol) : "memory");
}
__device__ __forceinline__ bool elect_one() {
    uint32_t p; asm volatile("{ .reg .pred p; elect.sync _|p, 0xffffffff; selp.u32 %0, 1, 0, p; }" : "=r"(p)); return p != 0;
}
__device__ __forceinline__ uint32_t mapa(uint32_t a, uint32_t cta) {
    uint32_t r; asm("mapa.shared::cluster.u32 %0, %1, %2;" : "=r"(r) : "r"(a), "r"(cta)); return r;
}
__device__ __forceinline__ void st_async(uint32_t dst, uint32_t bar, float x, float y, float z, float w) {
    asm volatile("st.async.shared::cluster.mbarrier::complete_tx::bytes.v4.f32 [%0], {%2,%3,%4,%5}, [%1];"
                 :: "r"(dst), "r"(bar), "f"(x), "f"(y), "f"(z), "f"(w) : "memory");
}
__device__ __forceinline__ uint32_t atom_inc(unsigned int* p, uint32_t wrap) {
    uint32_t r; asm volatile("atom.relaxed.gpu.global.inc.u32 %0, [%1], %2;" : "=r"(r) : "l"(p), "r"(wrap) : "memory"); return r;
}
__device__ __forceinline__ uint32_t ld_relaxed(const unsigned int* p) {
    uint32_t r; asm volatile("ld.relaxed.gpu.global.u32 %0, [%1];" : "=r"(r) : "l"(p) : "memory"); return r;
}
__device__ __forceinline__ int4 lds128i(uint32_t a) {
    int4 v; asm volatile("ld.shared.v4.s32 {%0,%1,%2,%3}, [%4];" : "=r"(v.x), "=r"(v.y), "=r"(v.z), "=r"(v.w) : "r"(a)); return v;
}
__device__ __forceinline__ float4 lds128f(uint32_t a) {
    float4 v; asm volatile("ld.shared.v4.f32 {%0,%1,%2,%3}, [%4];" : "=f"(v.x), "=f"(v.y), "=f"(v.z), "=f"(v.w) : "r"(a)); return v;
}
__device__ __forceinline__ uint2 lds64(uint32_t a) {
    uint2 v; asm volatile("ld.shared.v2.u32 {%0,%1}, [%2];" : "=r"(v.x), "=r"(v.y) : "r"(a)); return v;
}
__device__ __forceinline__ float lds32f(uint32_t a) {
    float v; asm volatile("ld.shared.f32 %0, [%1];" : "=f"(v) : "r"(a)); return v;
}
__device__ __forceinline__ void sts128f(uint32_t a, float x, float y, float z, float w) {
    asm volatile("st.shared.v4.f32 [%0], {%1,%2,%3,%4};" :: "r"(a), "f"(x), "f"(y), "f"(z), "f"(w) : "memory");
}
__device__ __forceinline__ void sts32f_if(int on, uint32_t a, float x) {
    asm volatile("{ .reg .pred p; setp.ne.s32 p, %0, 0; @p st.shared.f32 [%1], %2; }" :: "r"(on), "r"(a), "f"(x) : "memory");
}
__device__ __forceinline__ float bf_lo(uint32_t v) { return __uint_as_float(v << 16); }
__device__ __forceinline__ float bf_hi(uint32_t v) { return __uint_as_float(v & 0xffff0000u); }
__device__ __forceinline__ float exp_diff(float a, float b) {
    float y; asm("ex2.approx.ftz.f32 %0, %1;" : "=f"(y) : "f"((a - b) * 1.4426950408889634f)); return y;
}
__device__ __forceinline__ uint32_t pack_bf16(float lo, float hi) {
    uint32_t r; asm("cvt.rn.bf16x2.f32 %0, %1, %2;" : "=r"(r) : "f"(hi), "f"(lo)); return r;
}
__device__ __forceinline__ uint32_t dequant2(int a, int b, uint32_t z, uint32_t s) {
    uint32_t x = pack_bf16((float)a, (float)b);
    asm("sub.rn.bf16x2 %0, %0, %1;" : "+r"(x) : "r"(z));
    asm("mul.rn.bf16x2 %0, %0, %1;" : "+r"(x) : "r"(s));
    return x;
}
__device__ __forceinline__ void mma_bf16(float (&d)[4], uint32_t a0, uint32_t a1, uint32_t a2, uint32_t a3, uint32_t b0, uint32_t b1) {
    asm("mma.sync.aligned.m16n8k16.row.col.f32.bf16.bf16.f32 {%0,%1,%2,%3}, {%4,%5,%6,%7}, {%8,%9}, {%0,%1,%2,%3};"
        : "+f"(d[0]), "+f"(d[1]), "+f"(d[2]), "+f"(d[3]) : "r"(a0), "r"(a1), "r"(a2), "r"(a3), "r"(b0), "r"(b1));
}
__device__ __forceinline__ void mma_tf32(float (&d)[4], float a0, float a1, float a2, float a3, float b0, float b1) {
    asm("mma.sync.aligned.m16n8k8.row.col.f32.tf32.tf32.f32 {%0,%1,%2,%3}, {%4,%5,%6,%7}, {%8,%9}, {%0,%1,%2,%3};"
        : "+f"(d[0]), "+f"(d[1]), "+f"(d[2]), "+f"(d[3])
        : "r"(__float_as_uint(a0)), "r"(__float_as_uint(a1)), "r"(__float_as_uint(a2)), "r"(__float_as_uint(a3)),
          "r"(__float_as_uint(b0)), "r"(__float_as_uint(b1)));
}

__global__ void __cluster_dims__(CPH, 1, 1) __launch_bounds__(NTHREADS, 1)
kv_decode_kernel(const char* __restrict__ qk, const char* __restrict__ qv,
                 const char* __restrict__ ks, const char* __restrict__ kz,
                 const char* __restrict__ vs, const char* __restrict__ vz, const char* __restrict__ q,
                 __nv_bfloat16* __restrict__ out, unsigned int* __restrict__ pace)
{
    extern __shared__ __align__(128) char smem[];
    const int tid   = threadIdx.x;
    const int head  = blockIdx.x / CPH;
    const int rank  = blockIdx.x % CPH;
    const int tile0 = head * TPH + rank;
    if (tid < 32)
        asm volatile("cp.async.bulk.prefetch.L2.global [%0], %1;" :: "l"(qk + (size_t)tile0 * TILE_B), "n"(TILE_B) : "memory");

    const uint32_t sb = (uint32_t)__cvta_generic_to_shared(smem);
    uint64_t pol;
    asm volatile("createpolicy.fractional.L2::evict_first.b64 %0, 1.0;" : "=l"(pol));

    auto issueK = [&](int n, int slot, int b) {
        mbar_expect_tx(sb + OFF_BK + 8 * b, TILE_B + SC_B);
        bulk_g2s(sb + OFF_RING + slot * SLOT_B, qk + (size_t)(tile0 + n * CPH) * TILE_B, TILE_B, sb + OFF_BK + 8 * b, pol);
    };
    auto issueS = [&](int n, int b) {
        const uint32_t bar = sb + OFF_BK + 8 * b, sc = sb + OFF_SC + b * SC_B;
        const size_t tile = tile0 + n * CPH;
        bulk_g2s(sc,                   ks + tile * KS_B, KS_B, bar, pol);
        bulk_g2s(sc + KS_B,            kz + tile * KS_B, KS_B, bar, pol);
        bulk_g2s(sc + 2 * KS_B,        vs + tile * VS_B, VS_B, bar, pol);
        bulk_g2s(sc + 2 * KS_B + VS_B, vz + tile * VS_B, VS_B, bar, pol);
    };
    auto issueV = [&](int n, int slot, int b) {
        mbar_expect_tx(sb + OFF_BV + 8 * b, TILE_B);
        #pragma unroll
        for (int p = 0; p < 4; p++)
            bulk_g2s(sb + OFF_RING + slot * SLOT_B + p * VP_PITCH, qv + (size_t)(tile0 + n * CPH) * TILE_B + p * VP_B,
                     VP_B, sb + OFF_BV + 8 * b, pol);
    };

    constexpr int NFIRST = 4;
    if (tid < 32 && elect_one()) {
        #pragma unroll
        for (int s = 0; s < NFIRST; s++) mbar_init(sb + OFF_BK + 8 * s, 1);
        #pragma unroll
        for (int s = 0; s < NFIRST; s++) issueK(s, s, s);
        #pragma unroll
        for (int s = 0; s < NSLOT; s++) {
            if (s >= NFIRST) mbar_init(sb + OFF_BK + 8 * s, 1);
            mbar_init(sb + OFF_BV + 8 * s, 1);
            mbar_init(sb + OFF_BE + 8 * s, NVW / 2);
        }
        #pragma unroll
        for (int s = 0; s < NPS + 6; s++) mbar_init(sb + OFF_BP + 8 * s, 1);
        #pragma unroll
        for (int s = 0; s < 4; s++) mbar_expect_tx(sb + OFF_BO + 8 * s, 2 * CPH * 32 * 4);
        mbar_expect_tx(sb + OFF_BM, CPH * NKW * 16);
        asm volatile("fence.mbarrier_init.release.cluster;" ::: "memory");
    }
    __syncwarp();
    asm volatile("barrier.cluster.arrive.relaxed.aligned;" ::: "memory");
    const int lane = tid & 31;
    const int w = __shfl_sync(0xffffffffu, tid >> 5, 0);

    if (w == 0) {
        if (elect_one()) {
            mbar_expect_tx(sb + OFF_BQ, Q_B);
            bulk_g2s(sb + OFF_Q, q + (size_t)head * Q_B, Q_B, sb + OFF_BQ, pol);
            #pragma unroll 1
            for (int s = 0; s < LEAD; s++) {
                if (s >= NFIRST) issueK(s, s, s);
                issueS(s, s);
            }
            int slot = LEAD, ph = 1, nk = LEAD, bk = LEAD, nv = 0, bv = 0;
            auto next = [&](bool k) {
                mbar_wait(sb + OFF_BE + 8 * slot, ph);
                if (k) {
                    issueK(nk, slot, bk);
                    issueS(nk, bk);
                    nk++;
                    if (++bk == NSLOT) bk = 0;
                } else {
                    issueV(nv, slot, bv);
                    nv++;
                    if (++bv == NSLOT) bv = 0;
                }
                if (++slot == NSLOT) { slot = 0; ph ^= 1; }
            };
            constexpr int NSTEP = NIT - LEAD / 2;
            uint32_t pend = 0;
            int seen = 0, budget = 1 << 13;
            #pragma unroll 1
            for (int n = 0; n < NSTEP; n++) {
                const int need = n * NCTA - (n < NSTEP - NEND ? SLACK : SLACK_END);
                if (seen < need) {
                    seen = (int)pend;
                    while (seen < need && budget > 0) { seen = (int)ld_relaxed(pace); budget--; }
                }
                pend = atom_inc(pace, NSTEP * NCTA - 1);
                next(nk < NIT);
                next(false);
            }
        }
        __syncwarp();
        asm volatile("barrier.cluster.wait.aligned;" ::: "memory");
        return;
    }
    asm volatile("barrier.cluster.wait.aligned;" ::: "memory");
    const int g = lane >> 2, t = lane & 3;

    if (w <= NVW) {
        const int set = (w - 1) >> 2, wq = (w - 1) & 3;
        const uint32_t voff  = t * VP_PITCH + (8 * wq + g) * 16;
        const uint32_t o_dst = mapa(sb + OFF_IO + (rank * 2 + set) * (DH * 4) + (8 * wq + g) * 16, t);
        const uint32_t o_bar = mapa(sb + OFF_BO + 8 * wq, t);
        float o[4] = {0.f, 0.f, 0.f, 0.f}, M = -FLT_MAX;
        int sv = set, phv = 0, sp = set, php = 0;
        mbar_wait(sb + OFF_BP + 8 * sp, php);
        float4 pa = lds128f(sb + OFF_P + sp * PS_B + lane * 16);
        float4 pb = lds128f(sb + OFF_P + sp * PS_B + 512 + lane * 16);
        float  mt = lds32f(sb + OFF_P + sp * PS_B + 1024 + t * 4);
        #pragma unroll 1
        for (int it = 0; it < NIT / 2; it++) {
            const float pu[8] = {pa.x, pa.y, pa.z, pa.w, pb.x, pb.y, pb.z, pb.w};
            const float Mn = fmaxf(M, mt);
            const float alpha = exp_diff(M, Mn), beta = exp_diff(mt, Mn);
            M = Mn;
            o[0] *= alpha; o[1] *= alpha; o[2] *= alpha; o[3] *= alpha;
            if (it + 1 < NIT / 2) {
                sp += 2;
                if (sp >= NPS) { sp -= NPS; php ^= 1; }
                mbar_wait(sb + OFF_BP + 8 * sp, php);
                pa = lds128f(sb + OFF_P + sp * PS_B + lane * 16);
                pb = lds128f(sb + OFF_P + sp * PS_B + 512 + lane * 16);
                mt = lds32f(sb + OFF_P + sp * PS_B + 1024 + t * 4);
            }
            const int slot = slot_of_v(2 * it + set);
            const uint32_t vb = sb + OFF_RING + slot * SLOT_B + voff, vbar = sb + OFF_BV + 8 * sv;
            const int ph = phv;
            sv += 2;
            if (sv >= NSLOT) { sv -= NSLOT; phv ^= 1; }

            mbar_wait(vbar, ph);
            float e0[4] = {0.f, 0.f, 0.f, 0.f}, e1[4] = {0.f, 0.f, 0.f, 0.f};
            #pragma unroll
            for (int j = 0; j < 4; j++) {
                const int4 va = lds128i(vb + (2 * j) * 512), vc = lds128i(vb + (2 * j + 1) * 512);
                mma_tf32(e0, (float)va.x, (float)va.y, (float)vc.x, (float)vc.y, pu[2 * j], pu[2 * j + 1]);
                mma_tf32(e1, (float)va.z, (float)va.w, (float)vc.z, (float)vc.w, pu[2 * j], pu[2 * j + 1]);
            }
            __syncwarp();
            mbar_arrive_if(lane == 0, sb + OFF_BE + 8 * slot);
            o[0] = fmaf(e0[0] + e0[1], beta, o[0]); o[1] = fmaf(e0[2] + e0[3], beta, o[1]);
            o[2] = fmaf(e1[0] + e1[1], beta, o[2]); o[3] = fmaf(e1[2] + e1[3], beta, o[3]);
        }
        st_async(o_dst, o_bar, o[0], o[1], o[2], o[3]);
        return;
    }

    const int kw = w - NVW - 1;
    {
        const uint32_t koff = (8 * (g >> 1) + (g & 1)) * 512 + (t + 4 * (g & 1)) * 16;
        const uint32_t soff = (t + 4 * (g & 1)) * 8;
        const uint32_t keep = (g & 1) ? 0xffffffffu : 0xffffe000u, drop = (g & 1) ? 0xffffe000u : 0u;
        const float SCALE = 0.08838834764831845f;

        uint2 qa[4][2];
        mbar_wait(sb + OFF_BQ, 0);
        #pragma unroll
        for (int c = 0; c < 4; c++) {
            qa[c][0] = lds64(sb + OFF_Q + (g >> 1) * (DH * 2) + (8 * c + t) * 8);
            qa[c][1] = lds64(sb + OFF_Q + (g >> 1) * (DH * 2) + (8 * c + t + 4) * 8);
        }
        float m = -FLT_MAX, l = 0.f, zs = 0.f;
        int sk = kw, phk = 0, sp = kw;
        #pragma unroll 1
        for (int it = kw; it < NIT; it += NKW) {
            const int slot = slot_of_k(it);
            const uint32_t kb = sb + OFF_RING + slot * SLOT_B, sc = sb + OFF_SC + sk * SC_B;
            mbar_wait(sb + OFF_BK + 8 * sk, phk);
            float d[4][4];
            #pragma unroll
            for (int j = 0; j < 4; j++) d[j][0] = d[j][1] = d[j][2] = d[j][3] = 0.f;
            #pragma unroll
            for (int c = 0; c < 4; c++) {
                #pragma unroll
                for (int u = 0; u < 2; u++) {
                    const uint2 z = lds64(sc + KS_B + (soff ^ (32 * u)) + c * 64), s = lds64(sc + (soff ^ (32 * u)) + c * 64);
                    #pragma unroll
                    for (int j = 0; j < 4; j++) {
                        const int4 k = lds128i(kb + (koff ^ (64 * u)) + j * 1024 + c * 128);
                        mma_bf16(d[j], qa[c][u].x, qa[c][u ^ 1].x, qa[c][u].y, qa[c][u ^ 1].y,
                                 dequant2(k.x, k.y, z.x, s.x), dequant2(k.z, k.w, z.y, s.y));
                    }
                }
            }
            const int4 vs8 = lds128i(sc + 2 * KS_B + t * 16), vz8 = lds128i(sc + 2 * KS_B + VS_B + t * 16);
            __syncwarp();
            mbar_arrive_if(lane < NVW / 2, sb + OFF_BE + 8 * slot);
            sk += NKW;
            if (sk >= NSLOT) { sk -= NSLOT; phk ^= 1; }

            float s[8];
            #pragma unroll
            for (int j = 0; j < 4; j++) {
                const uint32_t x = pack_bf16(d[j][0], d[j][3]);
                const uint32_t y = pack_bf16(bf_lo(x) * SCALE, bf_hi(x) * SCALE);
                s[2 * j] = bf_lo(y); s[2 * j + 1] = bf_hi(y);
            }
            float mx = fmaxf(fmaxf(fmaxf(s[0], s[1]), fmaxf(s[2], s[3])), fmaxf(fmaxf(s[4], s[5]), fmaxf(s[6], s[7])));
            if (__any_sync(0xffffffffu, mx > m)) {
                mx = fmaxf(mx, __shfl_xor_sync(0xffffffffu, mx, 1));
                mx = fmaxf(mx, __shfl_xor_sync(0xffffffffu, mx, 2));
                mx = fmaxf(mx, m);
                const float corr = exp_diff(m, mx);
                m = mx; l *= corr; zs *= corr;
            }
            const uint32_t vsr[4] = {(uint32_t)vs8.x, (uint32_t)vs8.y, (uint32_t)vs8.z, (uint32_t)vs8.w};
            const uint32_t vzr[4] = {(uint32_t)vz8.x, (uint32_t)vz8.y, (uint32_t)vz8.z, (uint32_t)vz8.w};
            float part[8];
            #pragma unroll
            for (int i = 0; i < 8; i++) {
                const float p  = exp_diff(s[i], m);
                const float pv = p * ((i & 1) ? bf_hi(vsr[i >> 1]) : bf_lo(vsr[i >> 1]));
                l += p;
                zs = fmaf(pv, (i & 1) ? bf_hi(vzr[i >> 1]) : bf_lo(vzr[i >> 1]), zs);
                part[i] = __uint_as_float(__float_as_uint(pv) & keep) - __uint_as_float(__float_as_uint(pv) & drop);
            }
            const uint32_t pd = sb + OFF_P + sp * PS_B;
            sts128f(pd + lane * 16, part[0], part[1], part[2], part[3]);
            sts128f(pd + 512 + lane * 16, part[4], part[5], part[6], part[7]);
            sts32f_if((lane & 7) == 0, pd + 1024 + (g >> 1) * 4, m);
            __syncwarp();
            mbar_arrive_if(lane == 0, sb + OFF_BP + 8 * sp);
            sp += NKW;
            if (sp >= NPS) sp -= NPS;
        }
        l  += __shfl_xor_sync(0xffffffffu, l, 1);
        zs += __shfl_xor_sync(0xffffffffu, zs, 1);
        l  += __shfl_xor_sync(0xffffffffu, l, 2);
        zs += __shfl_xor_sync(0xffffffffu, zs, 2);
        if ((lane & 7) == 0)
            st_async(mapa(sb + OFF_IM + (rank * NKW + kw) * 16, g >> 1), mapa(sb + OFF_BM, g >> 1), m, l, zs, 0.f);
        __syncwarp();
    }

    mbar_wait_cluster(sb + OFF_BM, 0);
    const float4 ml = lds128f(sb + OFF_IM + (lane & 15) * 16);
    const float mv = fmaxf(ml.x, __shfl_xor_sync(0xffffffffu, ml.x, 2));
    float M = fmaxf(mv, __shfl_xor_sync(0xffffffffu, mv, 1));
    M = fmaxf(M, __shfl_xor_sync(0xffffffffu, M, 4));
    M = fmaxf(M, __shfl_xor_sync(0xffffffffu, M, 8));
    const float cw = exp_diff(ml.x, M);
    float L = ml.y * cw, Z = ml.z * cw;
    #pragma unroll
    for (int x = 1; x <= 8; x <<= 1) {
        L += __shfl_xor_sync(0xffffffffu, L, x);
        Z += __shfl_xor_sync(0xffffffffu, Z, x);
    }
    const float inv = 1.f / L, cv = exp_diff(mv, M) * inv;
    float c[2 * CPH];
    #pragma unroll
    for (int x = 0; x < 2 * CPH; x++) c[x] = __shfl_sync(0xffffffffu, cv, (x >> 1) * NKW + (x & 1));
    float a = -Z * inv, b = 0.f;
    const uint32_t src = __shfl_sync(0xffffffffu, sb + OFF_IO + (32 * kw + lane) * 4, lane);
    __nv_bfloat16* dst = (__nv_bfloat16*)__shfl_sync(0xffffffffu, (unsigned long long)(out + blockIdx.x * DH + 32 * kw + lane), lane);
    mbar_wait_cluster(sb + OFF_BO + 8 * kw, 0);
    #pragma unroll
    for (int x = 0; x < 2 * CPH; x += 2) {
        a = fmaf(lds32f(src + x * (DH * 4)), c[x], a);
        b = fmaf(lds32f(src + (x + 1) * (DH * 4)), c[x + 1], b);
    }
    __stcg(dst, __float2bfloat16_rn(a + b));
}

}

extern "C" void kernel_launch(void* const* d_in, const int* in_sizes, int n_in, void* d_out, int out_size) {
    (void)in_sizes; (void)n_in; (void)out_size;
    static unsigned int* pace = nullptr;
    if (!pace) {
        cudaFuncSetAttribute(kv_decode_kernel, cudaFuncAttributeMaxDynamicSharedMemorySize, SMEM_B);
        cudaGetSymbolAddress((void**)&pace, g_pace);
    }
    kv_decode_kernel<<<NCTA, NTHREADS, SMEM_B>>>(
        (const char*)d_in[1], (const char*)d_in[2], (const char*)d_in[3], (const char*)d_in[4],
        (const char*)d_in[5], (const char*)d_in[6], (const char*)d_in[0], (__nv_bfloat16*)d_out, pace);
}
```
